```python
import torch

def _softmax(x, axis=-1):
    return torch.softmax(x, dim=axis)
def _gelu(x):
    return torch.nn.functional.gelu(x, approximate="tanh")
def _silu(x):
    return torch.nn.functional.silu(x)
def _sigmoid(x):
    return torch.sigmoid(x)
def _layernorm(x, axis=-1, eps=1e-5):
    m = x.mean(dim=axis, keepdim=True)
    v = x.var(dim=axis, keepdim=True, unbiased=False)
    return (x - m) / torch.sqrt(v + eps)
def _scatter_add(tgt, idx, src, axis=0):
    return tgt.clone().index_add_(axis, idx, src)
def _segment_sum(src, seg, n):
    out = torch.zeros((n,) + src.shape[1:], dtype=src.dtype)
    return out.index_add_(0, seg, src)
def _pad(x, pw):
    flat = tuple(v for pair in reversed(pw) for v in pair)
    return torch.nn.functional.pad(x, flat)

kernel_name = 'sequential_preLN__sliding_block_cached__dense_activation_relu__decode'

def setup_inputs():

    _w = (lambda a: (lambda t: t.to(torch.bfloat16) if t.is_floating_point() else t)(torch.as_tensor(a)))
    def _A_setup():
        B, Sq, D = 8, 1, 576
        Hq, Hkv, Sk, Dh = 32, 16, 8192, 128
        assert Hq % Hkv == 0, (Hq, Hkv)
        return {
            "x": _w((lambda *s: torch.randn(*s, dtype=torch.bfloat16) * 0.05)(B, Sq, D)),
            "k_cache": _w((lambda *s: torch.randn(*s, dtype=torch.bfloat16) * 3.2)(B, Hkv, Sk, Dh)),
            "v_cache": _w((lambda *s: torch.randn(*s, dtype=torch.bfloat16) * 0.4)(B, Hkv, Sk, Dh)),
            "wq": _w((lambda *s: torch.randn(*s, dtype=torch.bfloat16) * 3.2)(D, Hq * Dh) * (D ** -0.5)),
            "wo": _w((lambda *s: torch.randn(*s, dtype=torch.bfloat16) * 0.4)(Hq * Dh, D) * ((Hq * Dh) ** -0.5)),
        }
    _A_in = _A_setup()

    def _B_setup():
        B, S, D, Dff = 8, 1, 576, 4608
        return {
            "x": _w((lambda *s: torch.randn(*s, dtype=torch.bfloat16) * 0.05)(B, S, D)),
            "w1": _w((lambda *s: torch.randn(*s, dtype=torch.bfloat16) * 0.05)(D, Dff)),
            "w2": _w((lambda *s: torch.randn(*s, dtype=torch.bfloat16) * 0.05)(Dff, D)),
        }
    _B_in = _B_setup()

    return {
        "A_x": _A_in["x"],
        "A_k_cache": _A_in["k_cache"],
        "A_v_cache": _A_in["v_cache"],
        "A_wq": _A_in["wq"],
        "A_wo": _A_in["wo"],
        "B_x": _B_in["x"],
        "B_w1": _B_in["w1"],
        "B_w2": _B_in["w2"],
    }

def reference(A_x, A_k_cache, A_v_cache, A_wq, A_wo, B_x, B_w1, B_w2):
    def _A_ref(x, k_cache, v_cache, wq, wo):
        B, Sq, D = x.shape
        Hq, Dh = 32, 128
        Hkv, Sk = k_cache.shape[1], k_cache.shape[2]
        W = min(4096, max(256, Sk // 4))
        rep = Hq // Hkv
        q = (lambda x, *d: x.permute(*d))((x @ wq).reshape(B, Sq, Hq, Dh), 0, 2, 1, 3)
        k = (lambda x, n, axis: torch.repeat_interleave(x, n, dim=axis))(k_cache[:, :, Sk - W:, :], rep, axis=1)
        v = (lambda x, n, axis: torch.repeat_interleave(x, n, dim=axis))(v_cache[:, :, Sk - W:, :], rep, axis=1)
        scores = torch.einsum("bhqd,bhkd->bhqk", q, k) * (Dh ** -0.5)
        p = _softmax(scores, axis=-1)
        o = torch.einsum("bhqk,bhkd->bhqd", p, v)
        return (lambda x, *d: x.permute(*d))(o, 0, 2, 1, 3).reshape(B, Sq, Hq * Dh) @ wo

    def _B_ref(x, w1, w2):
        h = torch.einsum("bsd,df->bsf", x, w1)
        zero = torch.zeros_like(h)
        h = torch.maximum(h, zero)
        return torch.einsum("bsf,fd->bsd", h, w2)

    x = A_x
    h = x + _A_ref(_layernorm(x, axis=-1), A_k_cache, A_v_cache, A_wq, A_wo)
    h2 = h + _B_ref(_layernorm(h, axis=-1), B_w1, B_w2)
    return h2
```

```cpp
#include <cuda_runtime.h>
#include <cuda_bf16.h>
#include <cuda.h>
#include <stdint.h>

namespace {

constexpr int D_MODEL = 576;
constexpr int NCTA = 128;
constexpr int NTHREADS = 320;
constexpr int SK = 8192;
constexpr int WIN = 2048;
constexpr int TILE_KEYS = 128;
constexpr int TILE_BYTES = TILE_KEYS * 256;
constexpr int NSLOT = 6;
constexpr int NTILE = WIN / TILE_KEYS;
#define PREWRITE 1
#define PREWRITE_TILE 30
#define LN_INLINE __forceinline__
#define HB_COPIES 4
#define PF_WO 999
#define PF_W1 999
#define PF_W2 999
#define GATE_THRESH 0
#define GATE_UNIT 63
#define PACE_NS 0
#define PACE_T0 0
#define WO_EARLY 4
#define H_LIGHT 1
#define A_LIGHT 0
#define W_START 4
#define W_BULK 4
#define W_END 2
#define B_BULK 8
#define B_END 66
#define BACKOFF_NS 100

constexpr int SM_SC = NSLOT * TILE_BYTES;
constexpr int SM_ACT = SM_SC + 10240;
constexpr int ACT_PITCH = 584;
constexpr int SM_GAT = SM_ACT + 8 * ACT_PITCH * 2;
constexpr int A_PITCH = 296;
constexpr int SM_QS = SM_GAT + 8 * A_PITCH * 2;
constexpr int SM_RED = SM_QS + 512;
constexpr int SM_BAR = SM_RED + 256;
constexpr int SM_TOTAL = SM_BAR + 256;
constexpr int SMEM_BYTES = SM_TOTAL + 1024;

constexpr int WQ_OFF = 4 * TILE_BYTES;
constexpr int WO_OFF = 2 * TILE_BYTES;
constexpr int WO_BYTES = 256 * 144;
constexpr int W1_OFF = WO_OFF + WO_BYTES;
constexpr int W1_BYTES = 576 * 80;
constexpr int W2_OFF = W1_OFF + W1_BYTES;
constexpr int W2_BYTES = 288 * 144;
constexpr int P_HEAD_STRIDE = 4096 + 64;
static_assert(W2_OFF + W2_BYTES <= NSLOT * TILE_BYTES, "weights do not fit");

constexpr int BAR_FULL = 0, BAR_EMPTY = 12, BAR_W = 18;
constexpr int NBOX = 71;

constexpr int QLL_OFF = 0;
constexpr int OLL_OFF = QLL_OFF + 16 * 8 * 128;
constexpr int HLL_OFF = OLL_OFF + 16 * 8 * 128;
constexpr int HB_OFF = HLL_OFF + 72 * 16 * 64;
constexpr int ALL_OFF = HB_OFF + HB_COPIES * 2304;
constexpr int YLL_OFF = ALL_OFF + 16 * 8 * 144;
constexpr int SCRATCH_U64 = YLL_OFF + 72 * 16 * 64;

struct __align__(64) Params {
    CUtensorMap tmK, tmV, tmWo, tmW1, tmW2;
    const __nv_bfloat16* x;
    const __nv_bfloat16* wq;
    const uint8_t *wo, *w1, *w2;
    __nv_bfloat16* out;
    unsigned long long* scratch;
    unsigned int* epoch;
};

__device__ unsigned long long g_scratch[SCRATCH_U64];
__device__ unsigned int g_epoch[32];

__device__ __forceinline__ uint32_t smem_u32(const void* p) { return (uint32_t)__cvta_generic_to_shared(p); }
__device__ __forceinline__ void mbar_init(uint32_t bar, uint32_t cnt) {
    asm volatile("mbarrier.init.shared::cta.b64 [%0], %1;" ::"r"(bar), "r"(cnt) : "memory");
}
__device__ __forceinline__ void mbar_expect_tx(uint32_t bar, uint32_t bytes) {
    asm volatile("mbarrier.arrive.expect_tx.shared::cta.b64 _, [%0], %1;" ::"r"(bar), "r"(bytes) : "memory");
}
__device__ __forceinline__ void mbar_arrive(uint32_t bar) {
    asm volatile("mbarrier.arrive.shared::cta.b64 _, [%0];" ::"r"(bar) : "memory");
}
__device__ __forceinline__ bool mbar_try(uint32_t bar, uint32_t parity) {
    uint32_t ok;
    asm volatile("{\n.reg .pred p;\nmbarrier.try_wait.parity.shared::cta.b64 p, [%1], %2;\nselp.u32 %0, 1, 0, p;\n}"
                 : "=r"(ok) : "r"(bar), "r"(parity) : "memory");
    return ok != 0;
}
constexpr uint32_t SPIN_LIMIT = 1u << 24;
__device__ __forceinline__ void mbar_wait(uint32_t bar, uint32_t parity) {
    uint32_t n = 0;
    while (!mbar_try(bar, parity)) {
        if (++n > SPIN_LIMIT) __trap();
    }
}
__device__ __forceinline__ void tma2d(uint32_t dst, const CUtensorMap* tm, int c0, int c1, uint32_t bar) {
    asm volatile("cp.async.bulk.tensor.2d.shared::cluster.global.mbarrier::complete_tx::bytes [%0], [%1, {%3, %4}], [%2];"
                 ::"r"(dst), "l"(tm), "r"(bar), "r"(c0), "r"(c1) : "memory");
}
__device__ __forceinline__ void l2_prefetch(const void* ptr, uint32_t bytes) {
    asm volatile("cp.async.bulk.prefetch.L2.global [%0], %1;" ::"l"(ptr), "r"(bytes) : "memory");
}
__device__ __forceinline__ void prefetch_tm(const CUtensorMap* tm) {
    asm volatile("prefetch.tensormap [%0];" ::"l"(tm) : "memory");
}
__device__ __forceinline__ void ldsm_x4(uint32_t (&r)[4], uint32_t addr) {
    asm volatile("ldmatrix.sync.aligned.m8n8.x4.shared.b16 {%0,%1,%2,%3}, [%4];"
                 : "=r"(r[0]), "=r"(r[1]), "=r"(r[2]), "=r"(r[3]) : "r"(addr) : "memory");
}
__device__ __forceinline__ void ldsm_x4_t(uint32_t (&r)[4], uint32_t addr) {
    asm volatile("ldmatrix.sync.aligned.m8n8.x4.trans.shared.b16 {%0,%1,%2,%3}, [%4];"
                 : "=r"(r[0]), "=r"(r[1]), "=r"(r[2]), "=r"(r[3]) : "r"(addr) : "memory");
}
__device__ __forceinline__ void ldsm_x2(uint32_t& r0, uint32_t& r1, uint32_t addr) {
    asm volatile("ldmatrix.sync.aligned.m8n8.x2.shared.b16 {%0,%1}, [%2];" : "=r"(r0), "=r"(r1) : "r"(addr) : "memory");
}
__device__ __forceinline__ void mma16816(float (&c)[4], const uint32_t (&a)[4], uint32_t b0, uint32_t b1) {
    asm volatile("mma.sync.aligned.m16n8k16.row.col.f32.bf16.bf16.f32 {%0,%1,%2,%3}, {%4,%5,%6,%7}, {%8,%9}, {%0,%1,%2,%3};"
                 : "+f"(c[0]), "+f"(c[1]), "+f"(c[2]), "+f"(c[3])
                 : "r"(a[0]), "r"(a[1]), "r"(a[2]), "r"(a[3]), "r"(b0), "r"(b1));
}
__device__ __forceinline__ unsigned long long ld_pkt(const unsigned long long* p) {
    unsigned long long v;
    asm volatile("ld.relaxed.gpu.global.u64 %0, [%1];" : "=l"(v) : "l"(p) : "memory");
    return v;
}
__device__ __forceinline__ void st_pkt(unsigned long long* p, uint32_t payload, uint32_t tag) {
    unsigned long long v = ((unsigned long long)tag << 32) | payload;
    asm volatile("st.relaxed.gpu.global.u64 [%0], %1;" ::"l"(p), "l"(v) : "memory");
}
template <int N, int STRIDE>
__device__ __forceinline__ void poll_pkts(const unsigned long long* p, uint32_t (&out)[N], uint32_t tag) {
    uint32_t n = 0;
    while (true) {
        unsigned long long v[N];
#pragma unroll
        for (int i = 0; i < N; i++) v[i] = ld_pkt(p + i * STRIDE);
        uint32_t bad[2] = {0u, 0u};
#pragma unroll
        for (int i = 0; i < N; i++) { bad[i & 1] |= (uint32_t)(v[i] >> 32) ^ tag; out[i] = (uint32_t)v[i]; }
        if ((bad[0] | bad[1]) == 0) break;
        if (++n > SPIN_LIMIT) __trap();
    }
}
__device__ __forceinline__ float ex2(float x) { float y; asm("ex2.approx.ftz.f32 %0, %1;" : "=f"(y) : "f"(x)); return y; }
__device__ __forceinline__ float bf16r(float x) { return __bfloat162float(__float2bfloat16_rn(x)); }
__device__ __forceinline__ uint32_t pack_bf16(float lo, float hi) {
    __nv_bfloat162 v = __floats2bfloat162_rn(lo, hi);
    return *reinterpret_cast<uint32_t*>(&v);
}
__device__ __forceinline__ float bf_lo(uint32_t v) { return __uint_as_float(v << 16); }
__device__ __forceinline__ float bf_hi(uint32_t v) { return __uint_as_float(v & 0xffff0000u); }
__device__ __forceinline__ float warp_sum(float v) {
#pragma unroll
    for (int o = 16; o > 0; o >>= 1) v += __shfl_xor_sync(0xffffffffu, v, o);
    return v;
}
__device__ __forceinline__ void sts32(uint32_t addr, uint32_t v) { asm volatile("st.shared.b32 [%0], %1;" ::"r"(addr), "r"(v) : "memory"); }
__device__ __forceinline__ void sts32f(uint32_t addr, float v) { asm volatile("st.shared.f32 [%0], %1;" ::"r"(addr), "f"(v) : "memory"); }
__device__ __forceinline__ uint32_t lds32(uint32_t addr) { uint32_t v; asm volatile("ld.shared.b32 %0, [%1];" : "=r"(v) : "r"(addr) : "memory"); return v; }
__device__ __forceinline__ float lds32f(uint32_t addr) { float v; asm volatile("ld.shared.f32 %0, [%1];" : "=f"(v) : "r"(addr) : "memory"); return v; }
__device__ __forceinline__ uint2 lds64(uint32_t addr) { uint2 v; asm volatile("ld.shared.v2.b32 {%0,%1}, [%2];" : "=r"(v.x), "=r"(v.y) : "r"(addr) : "memory"); return v; }
__device__ __forceinline__ uint4 lds128(uint32_t addr) { uint4 v; asm volatile("ld.shared.v4.b32 {%0,%1,%2,%3}, [%4];" : "=r"(v.x), "=r"(v.y), "=r"(v.z), "=r"(v.w) : "r"(addr) : "memory"); return v; }
__device__ __forceinline__ void sts64f(uint32_t addr, float a, float b) { asm volatile("st.shared.v2.f32 [%0], {%1,%2};" ::"r"(addr), "f"(a), "f"(b) : "memory"); }
__device__ __forceinline__ void sts128(uint32_t addr, uint4 v) { asm volatile("st.shared.v4.b32 [%0], {%1,%2,%3,%4};" ::"r"(addr), "r"(v.x), "r"(v.y), "r"(v.z), "r"(v.w) : "memory"); }

__device__ __forceinline__ void layernorm_row(const uint32_t (&xv)[9], uint32_t dst_addr) {
    const float shift = bf_lo(__shfl_sync(0xffffffffu, xv[0], 0));
    float s0 = 0.f, s1 = 0.f, q0 = 0.f, q1 = 0.f;
#pragma unroll
    for (int i = 0; i < 9; i++) {
        const float d0 = bf_lo(xv[i]) - shift, d1 = bf_hi(xv[i]) - shift;
        s0 += d0; s1 += d1; q0 = fmaf(d0, d0, q0); q1 = fmaf(d1, d1, q1);
    }
    float s = s0 + s1, q = q0 + q1;
#pragma unroll
    for (int o = 16; o > 0; o >>= 1) { s += __shfl_xor_sync(0xffffffffu, s, o); q += __shfl_xor_sync(0xffffffffu, q, o); }
    const float dm = s * (1.0f / 576.0f);
    const float mean = shift + dm;
    const float var = fmaxf(fmaf(-dm, dm, q * (1.0f / 576.0f)), 0.f);
    float den, rcp;
    asm("sqrt.approx.ftz.f32 %0, %1;" : "=f"(den) : "f"(bf16r(bf16r(var) + 1e-5f)));
    asm("rcp.approx.ftz.f32 %0, %1;" : "=f"(rcp) : "f"(bf16r(den)));
    const __nv_bfloat162 mb2 = __float2bfloat162_rn(mean);
#pragma unroll
    for (int i = 0; i < 9; i++) {
        __nv_bfloat162 d2 = __hsub2(*reinterpret_cast<const __nv_bfloat162*>(&xv[i]), mb2);
        const uint32_t du = *reinterpret_cast<uint32_t*>(&d2);
        sts32(dst_addr + 128 * i, pack_bf16(bf_lo(du) * rcp, bf_hi(du) * rcp));
    }
}

template <int KSTEPS, int PITCH>
__device__ __forceinline__ void load_wfrags(uint32_t (&wf)[KSTEPS * 2], uint32_t lane_addr) {
#pragma unroll
    for (int i = 0; i < KSTEPS / 2; i++) {
        uint32_t r[4];
        ldsm_x4_t(r, lane_addr + i * 32 * PITCH);
        wf[4 * i] = r[0]; wf[4 * i + 1] = r[1]; wf[4 * i + 2] = r[2]; wf[4 * i + 3] = r[3];
    }
}
template <int NP, int DEPTH>
__device__ __forceinline__ void gemm_tile(float& o0, float& o1, const uint32_t (&wf)[NP * 4], uint32_t a_lane, int npairs) {
    float c[4][4];
#pragma unroll
    for (int i = 0; i < 4; i++) { c[i][0] = c[i][1] = c[i][2] = c[i][3] = 0.f; }
    uint32_t r[DEPTH][4];
#pragma unroll
    for (int i = 0; i < DEPTH; i++) ldsm_x4(r[i], a_lane + i * 64);
#pragma unroll
    for (int i = 0; i < NP; i++) {
        if (i < NP - 1 || npairs == NP) {
            mma16816(c[(i & 1) * 2], r[i % DEPTH], wf[4 * i], wf[4 * i + 1]);
            mma16816(c[(i & 1) * 2 + 1], r[i % DEPTH], wf[4 * i + 2], wf[4 * i + 3]);
        }
        if (i + DEPTH < NP) ldsm_x4(r[i % DEPTH], a_lane + (i + DEPTH) * 64);
    }
    o0 = (c[0][0] + c[2][0]) + (c[1][2] + c[3][2]);
    o1 = (c[0][1] + c[2][1]) + (c[1][3] + c[3][3]);
}
template <int ACT_P>
__device__ __forceinline__ uint32_t act_lane_off(int lane) { return (lane & 7) * ACT_P + ((((lane >> 3) & 1) << 1) | (lane >> 4)) * 16; }
template <class T> __device__ __forceinline__ T* pin(T* p) { asm volatile("mov.b64 %0, %0;" : "+l"(p)); return p; }
__device__ __forceinline__ uint32_t pin32(uint32_t v) { asm volatile("mov.b32 %0, %0;" : "+r"(v)); return v; }

__device__ __forceinline__ void ld_pkt2(const unsigned long long* p, unsigned long long& a, unsigned long long& b) {
    asm volatile("ld.relaxed.gpu.global.v2.u64 {%0,%1}, [%2];" : "=l"(a), "=l"(b) : "l"(p) : "memory");
}
__device__ __forceinline__ void st_pkt2(unsigned long long* p, uint32_t v0, uint32_t v1, uint32_t tag) {
    const unsigned long long a = ((unsigned long long)tag << 32) | v0, b = ((unsigned long long)tag << 32) | v1;
    asm volatile("st.relaxed.gpu.global.v2.u64 [%0], {%1,%2};" ::"l"(p), "l"(a), "l"(b) : "memory");
}
template <int N, int STRIDE>
__device__ __forceinline__ void poll_pairs(const unsigned long long* p, uint32_t (&out)[2 * N], uint32_t tag) {
    uint32_t n = 0;
    while (true) {
        unsigned long long v[2 * N];
#pragma unroll
        for (int i = 0; i < N; i++) ld_pkt2(p + i * STRIDE, v[2 * i], v[2 * i + 1]);
        uint32_t bad[4] = {0u, 0u, 0u, 0u};
#pragma unroll
        for (int i = 0; i < 2 * N; i++) { bad[i & 3] |= (uint32_t)(v[i] >> 32) ^ tag; out[i] = (uint32_t)v[i]; }
        if (((bad[0] | bad[1]) | (bad[2] | bad[3])) == 0) break;
        if (++n > SPIN_LIMIT) __trap();
    }
}
__device__ __forceinline__ void wait_first(const unsigned long long* p, uint32_t tag, int lane, bool backoff) {
    if (lane == 0) {
        uint32_t n = 0;
        while ((uint32_t)(ld_pkt(p) >> 32) != tag) {
            if (BACKOFF_NS && backoff) __nanosleep(BACKOFF_NS);
            if (++n > SPIN_LIMIT) __trap();
        }
    }
    __syncwarp();
}
__device__ __forceinline__ void sync_attn() { asm volatile("bar.sync 1, 256;" ::: "memory"); }
__device__ __forceinline__ void sync_comp() { asm volatile("bar.sync 2, 288;" ::: "memory"); }

#define TS(i) do { } while (0)

__global__ void __launch_bounds__(NTHREADS, 1)
fused_decode_kernel(const __grid_constant__ Params p) {
    extern __shared__ uint8_t smem_raw[];
    const uint32_t sb = (smem_u32(smem_raw) + 1023u) & ~1023u;
    const int tid = threadIdx.x, lane = tid & 31;
    const int warp = __shfl_sync(0xffffffffu, tid >> 5, 0);
    const int cta = blockIdx.x, g = cta >> 3, j = cta & 7;
    const uint32_t bars = sb + SM_BAR;

    if (warp == 9) {
        if (lane == 0) {
            TS(0);
#pragma unroll 1
            for (int i = 0; i < 25; i++) mbar_init(bars + i * 8, (i >= BAR_EMPTY && i < BAR_W) ? 8 : 1);
            asm volatile("fence.mbarrier_init.release.cluster;" ::: "memory");
            asm volatile("fence.proxy.async.shared::cta;" ::: "memory");
        }
        const int row0 = (j * 16 + g) * SK + (SK - WIN);
#pragma unroll 1
        for (int it = 0; it < NBOX; it++) {
            if (it == W_START) __syncthreads();
            const int i = it < 64 - WO_EARLY ? it : (it < 66 - WO_EARLY ? it + WO_EARLY : (it < 66 ? it - 2 : it));
            if (lane == 0) {
                if (i == PF_WO) l2_prefetch(p.wo + cta * WO_BYTES, WO_BYTES);
                if (i == PF_W1) l2_prefetch(p.w1 + cta * W2_BYTES, W2_BYTES);
                if (i == PF_W2) l2_prefetch(p.w2 + cta * W2_BYTES, W2_BYTES);
                if (it == 66 && GATE_THRESH > 0) {
                    uint32_t ep, cnt, n = 0;
                    asm volatile("ld.relaxed.gpu.global.u32 %0, [%1];" : "=r"(ep) : "l"(p.epoch) : "memory");
                    do {
                        asm volatile("ld.relaxed.gpu.global.u32 %0, [%1];" : "=r"(cnt) : "l"(p.epoch + 16) : "memory");
                        if (++n > SPIN_LIMIT) __trap();
                    } while ((int)(cnt - (ep * NCTA + GATE_THRESH)) < 0);
                }
                const int mt = it - (it < B_BULK ? W_START : (it < B_END ? W_BULK : W_END));
                const int m = mt < 64 - WO_EARLY ? mt : (mt < 66 - WO_EARLY ? mt + WO_EARLY : (mt < 66 ? mt - 2 : mt));
                if (m >= 0) mbar_wait(bars + (m < 64 ? BAR_FULL + m % (2 * NSLOT) : BAR_W + m - 64) * 8, m < 64 ? (m / (2 * NSLOT)) & 1 : 0);
                const int r = i < 64 ? ((i & 1) ? -3 : (i >> 1) - NSLOT) : 26 + ((i - 63) >> 1);
                if (r >= -2) {
                    const int slot = (r + NSLOT) % NSLOT;
                    mbar_wait(bars + (BAR_EMPTY + slot) * 8, ((r + NSLOT) / NSLOT - 1 + (slot >= 4 ? 1 : 0)) & 1);
                }
                const CUtensorMap* tm;
                uint32_t dst, bar, bytes;
                int c0, c1;
                if (i < 64) {
                    tm = i < 32 ? &p.tmK : &p.tmV;
                    bar = i % (2 * NSLOT); dst = (bar >> 1) * TILE_BYTES + (i & 1) * (TILE_BYTES / 4); bar += BAR_FULL; bytes = TILE_BYTES / 2;
                    c0 = 0; c1 = row0 + (i & 31) * (TILE_KEYS / 2);
                } else {
                    bar = BAR_W + i - 64;
                    if (i < 66) { tm = &p.tmWo; bytes = 128 * 144; dst = WO_OFF + (i - 64) * bytes; c0 = j * 72; c1 = g * 256 + (i - 64) * 128; }
                    else if (i < 69) { tm = &p.tmW1; bytes = 192 * 80; dst = W1_OFF + (i - 66) * bytes; c0 = (g * 288 + j * 36) & ~7; c1 = (i - 66) * 192; }
                    else { tm = &p.tmW2; bytes = 144 * 144; dst = W2_OFF + (i - 69) * bytes; c0 = j * 72; c1 = g * 288 + (i - 69) * 144; }
                }
                bar = bars + bar * 8;
                mbar_expect_tx(bar, bytes);
                tma2d(sb + dst, tm, c0, c1, bar);
                if (i < 64) tma2d(sb + dst + TILE_BYTES / 2, tm, 64, c1, bar);
                if (i == GATE_UNIT) asm volatile("red.relaxed.gpu.global.add.u32 [%0], 1;" ::"l"(p.epoch + 16) : "memory");
                if (i >= 64) TS(i - 64 + 40); else if ((i & 1) == 0) TS(2 + (i >> 1));
            }
        }
        return;
    }

    const int g8 = lane >> 2, t4 = lane & 3;
    unsigned long long* const scratch = p.scratch;
    const bool is_attn = warp < 8;
    const bool is_red = (warp == 8) && (g < 9);
    uint32_t hv[9];
    uint32_t res = 0;
    if (is_attn) {
        const uint32_t* xr = reinterpret_cast<const uint32_t*>(p.x + warp * D_MODEL) + lane;
#pragma unroll
        for (int i = 0; i < 9; i++) hv[i] = __ldg(xr + 32 * i);
    } else if (is_red) {
        res = __ldg(reinterpret_cast<const uint32_t*>(p.x + g8 * D_MODEL + j * 72 + g * 8) + t4);
    }
    if (is_attn) {
        const __nv_bfloat16* src = p.wq + (tid >> 2) * 4096 + g * 256 + j * 32 + (tid & 3) * 8;
        uint32_t dst = sb + WQ_OFF + (tid >> 2) * 80 + (tid & 3) * 16;
#pragma unroll 1
        for (int i = 0; i < 9; i++) {
            asm volatile("cp.async.cg.shared.global [%0], [%1], 16;" ::"r"(dst), "l"(src) : "memory");
            src += 64 * 4096; dst += 64 * 80;
        }
        asm volatile("cp.async.commit_group;" ::: "memory");
    }
    uint32_t tag;
    asm volatile("ld.relaxed.gpu.global.u32 %0, [%1];" : "=r"(tag) : "l"(p.epoch) : "memory");
    const uint32_t q_out = QLL_OFF + (g * 8 + g8) * 128 + j * 16 + warp * 4 + t4;
    const uint32_t o_out = pin32(OLL_OFF + cta * 128 + ((lane >> 3) & 1) * 64 + warp * 8 + ((lane >> 2) & 1) * 4 + (lane & 3));
    const uint32_t part_out = pin32(HLL_OFF + ((warp * 8 + j) * 16 + g) * 64 + lane * 2);
    const int a_col = warp * 8 + 2 * t4 - (j & 1) * 4;
    const bool a_valid = warp < 5 && a_col >= 0 && a_col < 36;
    const uint32_t x_out = pin32(is_attn ? ALL_OFF + (g * 8 + g8) * 144 + j * 18 + (a_col >> 1) : HB_OFF + g8 * 288 + j * 36 + g * 4 + t4);
    const uint32_t x_in = pin32(HB_OFF + (cta % HB_COPIES) * 2304 + warp * 288 + lane);
    const uint32_t red_in = pin32(HLL_OFF + cta * 1024 + warp * 128 + lane * 2);
    const uint32_t ln_dst = pin32(sb + SM_ACT + warp * ACT_PITCH * 2 + lane * 4);
    const uint32_t gat_dst_a = pin32(sb + SM_GAT + (tid / 36) * (A_PITCH * 2) + (tid % 36) * 16);
    if (warp < 4) st_pkt(scratch + q_out, 0u, 0u);
    tag += 1;
    __syncthreads();
    TS(0);

#pragma unroll 1
    for (int ph = 0; ph < 2; ph++) {
        float o0, o1;
        if (is_attn) {
            uint32_t wf[72];
            if (ph == 0) {
                asm volatile("cp.async.wait_group 0;" ::: "memory");
                sync_attn();
            }
            if (warp < 5) {
                if (ph) { mbar_wait(bars + (BAR_W + 2) * 8, 0); mbar_wait(bars + (BAR_W + 3) * 8, 0); mbar_wait(bars + (BAR_W + 4) * 8, 0); }
                TS(2 + 10 * ph);
                load_wfrags<36, 80>(wf, sb + (ph ? W1_OFF : WQ_OFF) + lane * 80 + warp * 16);
                if (ph == 0) {
                    __syncwarp();
                    if (lane < (warp < 3 ? 2 : 1)) { mbar_arrive(bars + (BAR_EMPTY + 4) * 8); mbar_arrive(bars + (BAR_EMPTY + 5) * 8); }
                }
            }
            if (ph) {
                if (H_LIGHT) wait_first(scratch + x_in + 256, tag, lane, false);
                TS(25);
                poll_pkts<9, 32>(scratch + x_in, hv, tag);
                TS(10);
            }
            layernorm_row(hv, ln_dst);
            sync_attn();
            TS(1 + 10 * ph);
            if (warp < 5) {
                gemm_tile<18, 6>(o0, o1, wf, sb + SM_ACT + act_lane_off<ACT_PITCH * 2>(lane), 18);
                uint32_t f = pack_bf16(o0, o1);
                if (ph) f = pack_bf16(fmaxf(bf_lo(f), 0.f), fmaxf(bf_hi(f), 0.f));
                if (ph ? a_valid : (warp < 4)) st_pkt(scratch + (ph ? x_out : q_out), f, tag);
            }
            TS(ph ? 13 : 20);
            if (ph == 0) {
                if (tid < 128) {
                    uint32_t v[1];
                    poll_pkts<1, 1>(scratch + QLL_OFF + cta * 128 + tid, v, tag);
                    TS(21);
                    sts32(sb + SM_QS + ((tid & 64) + (tid & 3) * 16 + ((tid & 63) >> 2)) * 4, v[0]);
                }
                sync_attn();
                TS(3);
                uint32_t qf[16];
#pragma unroll
                for (int s = 0; s < 4; s++) {
                    const uint4 v = lds128(sb + SM_QS + ((g8 & 1) * 64 + t4 * 16) * 4 + s * 16);
                    qf[4 * s] = v.x; qf[4 * s + 1] = v.y; qf[4 * s + 2] = v.z; qf[4 * s + 3] = v.w;
                }

                float m0 = -INFINITY, m1 = -INFINITY;
                {
                    const int krow = warp * 16 + (lane & 7) + ((lane >> 3) & 1) * 8;
                    const uint32_t rowoff = krow * 128;
                    const uint32_t chi = lane >> 4;
                    const uint32_t sw = krow & 7;
                    uint32_t slot = 0, par = 0;
                    uint32_t wsc = sb + SM_SC + ((warp >> 1) * 40 + (warp & 1) * 16 + g8) * 4;
#pragma unroll 1
                    for (int n = 0; n < NTILE; n++) {
                        mbar_wait(bars + (BAR_FULL + 2 * slot + (warp >> 2)) * 8, par);
                        const uint32_t base = sb + slot * TILE_BYTES + rowoff;
                        float c0[4] = {0.f, 0.f, 0.f, 0.f}, c1[4] = {0.f, 0.f, 0.f, 0.f};
#pragma unroll
                        for (int s = 0; s < 8; s += 2) {
                            uint32_t a[4], b[4];
                            ldsm_x4(a, base + (s >> 2) * (TILE_BYTES / 2) + ((((s & 3) * 2 + chi) ^ sw) << 4));
                            ldsm_x4(b, base + (s >> 2) * (TILE_BYTES / 2) + ((((s & 3) * 2 + 2 + chi) ^ sw) << 4));
                            mma16816(c0, a, qf[2 * s], qf[2 * s + 1]);
                            mma16816(c1, b, qf[2 * s + 2], qf[2 * s + 3]);
                        }
                        __syncwarp();
                        if (lane == 0) mbar_arrive(bars + (BAR_EMPTY + slot) * 8);
                        const float scale = 0.08838834764831845f;
                        const uint32_t u0 = pack_bf16(c0[0] + c1[0], c0[1] + c1[1]), u1 = pack_bf16(c0[2] + c1[2], c0[3] + c1[3]);
                        const uint32_t s0 = pack_bf16(bf_lo(u0) * scale, bf_hi(u0) * scale), s1 = pack_bf16(bf_lo(u1) * scale, bf_hi(u1) * scale);
                        m0 = fmaxf(m0, fmaxf(bf_lo(s0), bf_lo(s1)));
                        m1 = fmaxf(m1, fmaxf(bf_hi(s0), bf_hi(s1)));
                        if (t4 == 0) { sts32(wsc, s0); sts32(wsc + 32, s1); }
                        wsc += 4 * 40 * 4;
                        if (++slot == NSLOT) { slot = 0; par ^= 1; }
                    }
                }
                TS(4);
                {
#pragma unroll
                    for (int o = 16; o > 2; o >>= 1) { m0 = fmaxf(m0, __shfl_xor_sync(0xffffffffu, m0, o)); m1 = fmaxf(m1, __shfl_xor_sync(0xffffffffu, m1, o)); }
                    if (lane == 0) { sts32f(sb + SM_RED + warp * 4, m0); sts32f(sb + SM_RED + 32 + warp * 4, m1); }
                    sync_attn();
                    {
                        const uint4 a = lds128(sb + SM_RED), b = lds128(sb + SM_RED + 16), c = lds128(sb + SM_RED + 32), d = lds128(sb + SM_RED + 48);
                        m0 = fmaxf(fmaxf(fmaxf(__uint_as_float(a.x), __uint_as_float(a.y)), fmaxf(__uint_as_float(a.z), __uint_as_float(a.w))),
                                   fmaxf(fmaxf(__uint_as_float(b.x), __uint_as_float(b.y)), fmaxf(__uint_as_float(b.z), __uint_as_float(b.w))));
                        m1 = fmaxf(fmaxf(fmaxf(__uint_as_float(c.x), __uint_as_float(c.y)), fmaxf(__uint_as_float(c.z), __uint_as_float(c.w))),
                                   fmaxf(fmaxf(__uint_as_float(d.x), __uint_as_float(d.y)), fmaxf(__uint_as_float(d.z), __uint_as_float(d.w))));
                    }
                    float e0[8], e1[8];
                    float s0 = 0.f, s1 = 0.f;
                    const float l2e = 1.4426950408889634f;
#pragma unroll
                    for (int i = 0; i < 4; i++) {
                        const uint2 v = lds64(sb + SM_SC + ((tid >> 2) * 40 + 2 * t4 + 8 * i) * 4);
                        e0[2 * i] = ex2((bf_lo(v.x) - m0) * l2e); e1[2 * i] = ex2((bf_hi(v.x) - m1) * l2e);
                        e0[2 * i + 1] = ex2((bf_lo(v.y) - m0) * l2e); e1[2 * i + 1] = ex2((bf_hi(v.y) - m1) * l2e);
                        s0 += e0[2 * i] + e0[2 * i + 1]; s1 += e1[2 * i] + e1[2 * i + 1];
                    }
                    s0 = warp_sum(s0); s1 = warp_sum(s1);
                    if (lane == 0) { sts32f(sb + SM_RED + 64 + warp * 4, s0); sts32f(sb + SM_RED + 96 + warp * 4, s1); }
                    sync_attn();
                    {
                        const uint4 a = lds128(sb + SM_RED + 64), b = lds128(sb + SM_RED + 80), c = lds128(sb + SM_RED + 96), d = lds128(sb + SM_RED + 112);
                        s0 = ((__uint_as_float(a.x) + __uint_as_float(a.y)) + (__uint_as_float(a.z) + __uint_as_float(a.w))) +
                             ((__uint_as_float(b.x) + __uint_as_float(b.y)) + (__uint_as_float(b.z) + __uint_as_float(b.w)));
                        s1 = ((__uint_as_float(c.x) + __uint_as_float(c.y)) + (__uint_as_float(c.z) + __uint_as_float(c.w))) +
                             ((__uint_as_float(d.x) + __uint_as_float(d.y)) + (__uint_as_float(d.z) + __uint_as_float(d.w)));
                    }
                    const float i0 = __fdividef(1.0f, s0), i1 = __fdividef(1.0f, s1);
                    sts128(sb + SM_SC + tid * 16, make_uint4(pack_bf16(e0[0] * i0, e0[1] * i0), pack_bf16(e0[2] * i0, e0[3] * i0),
                                                             pack_bf16(e0[4] * i0, e0[5] * i0), pack_bf16(e0[6] * i0, e0[7] * i0)));
                    sts128(sb + SM_SC + P_HEAD_STRIDE + tid * 16, make_uint4(pack_bf16(e1[0] * i1, e1[1] * i1), pack_bf16(e1[2] * i1, e1[3] * i1),
                                                                             pack_bf16(e1[4] * i1, e1[5] * i1), pack_bf16(e1[6] * i1, e1[7] * i1)));
                    sync_attn();
                }
                TS(5);
                float c0[4] = {0.f, 0.f, 0.f, 0.f}, c1[4] = {0.f, 0.f, 0.f, 0.f};
                {
                    const int krow = (lane & 7) + (lane >> 4) * 8;
                    const uint32_t chunk = (warp & 3) * 2 + ((lane >> 3) & 1);
                    const uint32_t lane_off = (warp >> 2) * (TILE_BYTES / 2) + krow * 128 + ((chunk ^ (lane & 7)) << 4);
                    uint32_t pb = sb + SM_SC + (g8 & 1) * P_HEAD_STRIDE + t4 * 16;
                    uint32_t slot = NTILE % NSLOT, par = (NTILE / NSLOT) & 1;
#pragma unroll 1
                    for (int n = NTILE; n < 2 * NTILE; n++) {
                        const uint32_t base = sb + slot * TILE_BYTES + lane_off;
#pragma unroll
                        for (int s = 0; s < 8; s += 2) {
                            if ((s & 3) == 0) mbar_wait(bars + (BAR_FULL + 2 * slot + (s >> 2)) * 8, par);
                            uint32_t a[4], b[4];
                            const uint4 pv = lds128(pb + (s >> 1) * 64);
                            ldsm_x4_t(a, base + s * 2048);
                            ldsm_x4_t(b, base + (s + 1) * 2048);
                            mma16816(c0, a, pv.x, pv.y);
                            mma16816(c1, b, pv.z, pv.w);
                        }
                        __syncwarp();
                        if (lane == 0) mbar_arrive(bars + (BAR_EMPTY + slot) * 8);
                        pb += 256;
                        if (++slot == NSLOT) { slot = 0; par ^= 1; }
                        if (n == PREWRITE_TILE) {
                            if (lane < 16) st_pkt(scratch + o_out, 0u, 0u);
                            st_pkt2(scratch + part_out, 0u, 0u, 0u); st_pkt2(scratch + part_out + (YLL_OFF - HLL_OFF), 0u, 0u, 0u);
                            if (a_valid) st_pkt(scratch + x_out, 0u, 0u);
                            if (warp == 0) asm volatile("bar.arrive 3, 64;" ::: "memory");
                        }
                    }
                }
                TS(6);
                const uint32_t pa = pack_bf16(c0[0] + c1[0], c0[1] + c1[1]);
                const uint32_t pb2 = pack_bf16(c0[2] + c1[2], c0[3] + c1[3]);
                const int src = (lane & 3) * 8;
                const uint32_t a0 = __shfl_sync(0xffffffffu, pa, src), a1 = __shfl_sync(0xffffffffu, pa, src + 4);
                const uint32_t b0 = __shfl_sync(0xffffffffu, pb2, src), b1 = __shfl_sync(0xffffffffu, pb2, src + 4);
                const uint32_t lo = (lane & 4) ? b0 : a0, hi = (lane & 4) ? b1 : a1;
                if (lane < 16) st_pkt(scratch + o_out, __byte_perm(lo, hi, (lane & 8) ? 0x7632 : 0x5410), tag);
                TS(22);
            }
        } else if (ph == 0) {
            asm volatile("bar.sync 3, 64;" ::: "memory");
            st_pkt2(scratch + part_out, 0u, 0u, 0u); st_pkt2(scratch + part_out + (YLL_OFF - HLL_OFF), 0u, 0u, 0u);
            if (is_red) {
#pragma unroll
                for (int r = 0; r < HB_COPIES; r++) st_pkt(scratch + x_out + r * 2304, 0u, 0u);
            }
        }

        {
            uint32_t wf[36];
            mbar_wait(bars + (BAR_W + 5 * ph) * 8, 0); mbar_wait(bars + (BAR_W + 5 * ph + 1) * 8, 0);
            TS(8 + 7 * ph);
            load_wfrags<18, 144>(wf, sb + (ph ? W2_OFF : WO_OFF) + lane * 144 + warp * 16);
            if (ph || is_attn) {
                uint32_t v[4];
                const unsigned long long* src = scratch + ((ph ? ALL_OFF + g * 1152 : OLL_OFF + g * 1024) + tid * 4);
                if (ph == 0 || A_LIGHT) wait_first(src, tag, lane, ph == 0);
                TS(23 + ph);
                poll_pairs<2, 2>(src, v, tag);
                sts128(ph ? gat_dst_a : sb + SM_GAT + warp * (A_PITCH * 2) + lane * 16, make_uint4(v[0], v[1], v[2], v[3]));
            }
            sync_comp();
            TS(7 + 7 * ph);
            gemm_tile<9, 9>(o0, o1, wf, sb + SM_GAT + act_lane_off<A_PITCH * 2>(lane), ph ? 9 : 8);
            st_pkt2(scratch + (part_out + (ph ? YLL_OFF - HLL_OFF : 0)), __float_as_uint(o0), __float_as_uint(o1), tag);
            TS(9 + 7 * ph);
        }
        if (g < 9) {
            if (is_attn) {
                uint32_t v[4];
                poll_pairs<2, 64>(scratch + (red_in + (ph ? YLL_OFF - HLL_OFF : 0)), v, tag);
                sts64f(sb + SM_SC + tid * 8, __uint_as_float(v[0]) + __uint_as_float(v[2]), __uint_as_float(v[1]) + __uint_as_float(v[3]));
            }
            TS(26 + ph);
            sync_comp();
            if (!is_attn) {
                float a[8], b[8];
#pragma unroll
                for (int w = 0; w < 8; w++) { const uint2 v = lds64(sb + SM_SC + w * 256 + lane * 8); a[w] = __uint_as_float(v.x); b[w] = __uint_as_float(v.y); }
                const float s0 = ((a[0] + a[1]) + (a[2] + a[3])) + ((a[4] + a[5]) + (a[6] + a[7]));
                const float s1 = ((b[0] + b[1]) + (b[2] + b[3])) + ((b[4] + b[5]) + (b[6] + b[7]));
                res = pack_bf16(bf_lo(res) + bf16r(s0), bf_hi(res) + bf16r(s1));
                if (ph == 0) {
#pragma unroll
                    for (int r = 0; r < HB_COPIES; r++) st_pkt(scratch + x_out + r * 2304, res, tag);
                    TS(10);
                } else {
                    *reinterpret_cast<uint32_t*>(p.out + g8 * D_MODEL + j * 72 + g * 8 + 2 * t4) = res;
                    TS(17);
                    if (cta == 0 && lane == 0) asm volatile("st.relaxed.gpu.global.u32 [%0], %1;" ::"l"(p.epoch), "r"(tag) : "memory");
                }
            }
        }
    }
}

typedef CUresult (*EncodeTiledFn)(CUtensorMap*, CUtensorMapDataType, cuuint32_t, void*, const cuuint64_t*, const cuuint64_t*,
                                  const cuuint32_t*, const cuuint32_t*, CUtensorMapInterleave, CUtensorMapSwizzle,
                                  CUtensorMapL2promotion, CUtensorMapFloatOOBfill);

void make_map(EncodeTiledFn enc, CUtensorMap* tm, const void* ptr, uint64_t cols, uint64_t rows, uint32_t box_cols, uint32_t box_rows,
              CUtensorMapSwizzle sw) {
    cuuint64_t gd[2] = {cols, rows};
    cuuint64_t gs[1] = {cols * 2};
    cuuint32_t bd[2] = {box_cols, box_rows};
    cuuint32_t es[2] = {1, 1};
    enc(tm, CU_TENSOR_MAP_DATA_TYPE_BFLOAT16, 2, const_cast<void*>(ptr), gd, gs, bd, es, CU_TENSOR_MAP_INTERLEAVE_NONE, sw,
        CU_TENSOR_MAP_L2_PROMOTION_L2_256B, CU_TENSOR_MAP_FLOAT_OOB_FILL_NONE);
}

}

extern "C" void kernel_launch(void* const* d_in, const int* in_sizes, int n_in, void* d_out, int out_size) {
    (void)in_sizes; (void)n_in; (void)out_size;
    static EncodeTiledFn enc = nullptr;
    static unsigned long long* scratch = nullptr;
    static unsigned int* epoch = nullptr;
    if (!enc) {
        cudaDriverEntryPointQueryResult qr;
        void* fn = nullptr;
        cudaGetDriverEntryPoint("cuTensorMapEncodeTiled", &fn, cudaEnableDefault, &qr);
        enc = (EncodeTiledFn)fn;
        cudaFuncSetAttribute(fused_decode_kernel, cudaFuncAttributeMaxDynamicSharedMemorySize, SMEM_BYTES);
        cudaGetSymbolAddress((void**)&scratch, g_scratch);
        cudaGetSymbolAddress((void**)&epoch, g_epoch);
    }
    Params p;
    make_map(enc, &p.tmK, d_in[1], 128, 8ull * 16 * SK, 64, TILE_KEYS / 2, CU_TENSOR_MAP_SWIZZLE_128B);
    make_map(enc, &p.tmV, d_in[2], 128, 8ull * 16 * SK, 64, TILE_KEYS / 2, CU_TENSOR_MAP_SWIZZLE_128B);
    make_map(enc, &p.tmWo, d_in[4], 576, 4096, 72, 128, CU_TENSOR_MAP_SWIZZLE_NONE);
    make_map(enc, &p.tmW1, d_in[6], 4608, 576, 40, 192, CU_TENSOR_MAP_SWIZZLE_NONE);
    make_map(enc, &p.tmW2, d_in[7], 576, 4608, 72, 144, CU_TENSOR_MAP_SWIZZLE_NONE);
    p.x = (const __nv_bfloat16*)d_in[0];
    p.wq = (const __nv_bfloat16*)d_in[3];
    p.wo = (const uint8_t*)d_in[4]; p.w1 = (const uint8_t*)d_in[6]; p.w2 = (const uint8_t*)d_in[7];
    p.out = (__nv_bfloat16*)d_out;
    p.scratch = scratch;
    p.epoch = epoch;
    fused_decode_kernel<<<NCTA, NTHREADS, SMEM_BYTES, cudaStreamPerThread>>>(p);
}
```

```cpp
#include <cuda_runtime.h>
#include <cuda_bf16.h>
#include <cuda.h>
#include <stdint.h>

namespace {

constexpr int D_MODEL = 576;
constexpr int NCTA = 128;
constexpr int NTHREADS = 320;
constexpr int SK = 8192;
constexpr int WIN = 2048;
constexpr int TILE_KEYS = 128;
constexpr int TILE_BYTES = TILE_KEYS * 256;
constexpr int NSLOT = 6;
constexpr int NTILE = WIN / TILE_KEYS;
#define PREWRITE_TILE 30
#define RED_DELAY 200
#define RED_DELAY0 800
#define A_DELAY 100
#define H_DELAY 0
#define H_BACKOFF 50
#define R0_BACKOFF 0
#define R1_BACKOFF 0
#define HB_COPIES 4
#define W_START 4
#define W_BULK 4
#define W_MIN 3
#define W_MAX 8
#define W_END 2
#define K_DELAY 2400
#define B_BULK 8
#define BAL_GAIN 16
#define BAL_SLEEP 200
#define BACKOFF_NS 100

constexpr int SM_SC = NSLOT * TILE_BYTES;
constexpr int SM_ACT = SM_SC + 12288;
constexpr int ACT_PITCH = 584;
constexpr int SM_GAT = SM_ACT + 8 * ACT_PITCH * 2;
constexpr int A_PITCH = 296;
constexpr int SM_QS = SM_GAT + 8 * A_PITCH * 2;
constexpr int SM_RED = SM_QS + 512;
constexpr int SM_WDYN = SM_RED + 192, SM_PROG = SM_RED + 196;
constexpr int SM_BAR = SM_RED + 256;
constexpr int SM_TOTAL = SM_BAR + 256;
constexpr int SMEM_BYTES = SM_TOTAL;

constexpr int WQ_OFF = 4 * TILE_BYTES;
constexpr int WO_OFF = 2 * TILE_BYTES;
constexpr int WO_BYTES = 256 * 144;
constexpr int W1_OFF = WO_OFF + WO_BYTES;
constexpr int W1_BYTES = 576 * 80;
constexpr int W2_OFF = W1_OFF + W1_BYTES;
constexpr int W2_BYTES = 288 * 144;
constexpr int P_HEAD_STRIDE = 4096 + 64;
static_assert(W2_OFF + W2_BYTES <= NSLOT * TILE_BYTES, "weights do not fit");

constexpr int BAR_FULL = 0, BAR_EMPTY = 12, BAR_W = 18;
constexpr int NITEM = 71;

constexpr int QLL_OFF = 0;
constexpr int OLL_OFF = QLL_OFF + 16 * 8 * 128;
constexpr int HLL_OFF = OLL_OFF + 16 * 8 * 128;
constexpr int HB_OFF = HLL_OFF + 72 * 16 * 64;
constexpr int ALL_OFF = HB_OFF + HB_COPIES * 2304;
constexpr int YLL_OFF = ALL_OFF + 16 * 8 * 144;
constexpr int SCRATCH_U64 = YLL_OFF + 72 * 16 * 64;

struct __align__(64) Params {
    CUtensorMap tmK, tmV, tmWo, tmW1, tmW2;
    const __nv_bfloat16* x;
    const __nv_bfloat16* wq;
    __nv_bfloat16* out;
    unsigned long long* scratch;
    unsigned int* epoch;
    int4 witem[7];
};

__device__ unsigned long long g_scratch[SCRATCH_U64];
__device__ unsigned int g_epoch[32];

__device__ __forceinline__ uint32_t smem_u32(const void* p) { return (uint32_t)__cvta_generic_to_shared(p); }
__device__ __forceinline__ void mbar_init(uint32_t bar, uint32_t cnt) {
    asm volatile("mbarrier.init.shared::cta.b64 [%0], %1;" ::"r"(bar), "r"(cnt) : "memory");
}
__device__ __forceinline__ void mbar_expect_tx(uint32_t bar, uint32_t bytes) {
    asm volatile("mbarrier.arrive.expect_tx.shared::cta.b64 _, [%0], %1;" ::"r"(bar), "r"(bytes) : "memory");
}
__device__ __forceinline__ void mbar_arrive(uint32_t bar) {
    asm volatile("mbarrier.arrive.shared::cta.b64 _, [%0];" ::"r"(bar) : "memory");
}
__device__ __forceinline__ bool mbar_try(uint32_t bar, uint32_t parity) {
    uint32_t ok;
    asm volatile("{\n.reg .pred p;\nmbarrier.try_wait.parity.shared::cta.b64 p, [%1], %2;\nselp.u32 %0, 1, 0, p;\n}"
                 : "=r"(ok) : "r"(bar), "r"(parity) : "memory");
    return ok != 0;
}
constexpr uint32_t SPIN_LIMIT = 1u << 24;
__device__ __forceinline__ void mbar_wait(uint32_t bar, uint32_t parity) {
    asm volatile("{\n.reg .pred p;\n.reg .u32 n;\nmov.u32 n, 0;\n"
                 "MBW_LOOP:\nmbarrier.try_wait.parity.shared::cta.b64 p, [%0], %1;\n@p bra MBW_DONE;\n"
                 "add.u32 n, n, 1;\nsetp.lt.u32 p, n, 16777216;\n@p bra MBW_LOOP;\ntrap;\nMBW_DONE:\n}"
                 ::"r"(bar), "r"(parity) : "memory");
}
template <int N>
__device__ __forceinline__ void mbar_wait_n(uint32_t bar) {
    uint32_t n = 0;
    while (true) {
        bool ok = true;
#pragma unroll
        for (int i = 0; i < N; i++) ok = mbar_try(bar + i * 8, 0) & ok;
        if (ok) break;
        if (++n > SPIN_LIMIT) __trap();
    }
}
__device__ __forceinline__ void tma2d(uint32_t dst, const CUtensorMap* tm, int c0, int c1, uint32_t bar) {
    asm volatile("cp.async.bulk.tensor.2d.shared::cluster.global.mbarrier::complete_tx::bytes [%0], [%1, {%3, %4}], [%2];"
                 ::"r"(dst), "l"(tm), "r"(bar), "r"(c0), "r"(c1) : "memory");
}
__device__ __forceinline__ void tma2d_hint(uint32_t dst, const CUtensorMap* tm, int c0, int c1, uint32_t bar, uint64_t pol) {
    asm volatile("cp.async.bulk.tensor.2d.shared::cluster.global.mbarrier::complete_tx::bytes.L2::cache_hint [%0], [%1, {%3, %4}], [%2], %5;"
                 ::"r"(dst), "l"(tm), "r"(bar), "r"(c0), "r"(c1), "l"(pol) : "memory");
}
__device__ __forceinline__ void ldsm_x4(uint32_t (&r)[4], uint32_t addr) {
    asm volatile("ldmatrix.sync.aligned.m8n8.x4.shared.b16 {%0,%1,%2,%3}, [%4];"
                 : "=r"(r[0]), "=r"(r[1]), "=r"(r[2]), "=r"(r[3]) : "r"(addr) : "memory");
}
__device__ __forceinline__ void ldsm_x4_t(uint32_t (&r)[4], uint32_t addr) {
    asm volatile("ldmatrix.sync.aligned.m8n8.x4.trans.shared.b16 {%0,%1,%2,%3}, [%4];"
                 : "=r"(r[0]), "=r"(r[1]), "=r"(r[2]), "=r"(r[3]) : "r"(addr) : "memory");
}
__device__ __forceinline__ void ldsm_x2(uint32_t& r0, uint32_t& r1, uint32_t addr) {
    asm volatile("ldmatrix.sync.aligned.m8n8.x2.shared.b16 {%0,%1}, [%2];" : "=r"(r0), "=r"(r1) : "r"(addr) : "memory");
}
__device__ __forceinline__ void mma16816(float (&c)[4], const uint32_t (&a)[4], uint32_t b0, uint32_t b1) {
    asm volatile("mma.sync.aligned.m16n8k16.row.col.f32.bf16.bf16.f32 {%0,%1,%2,%3}, {%4,%5,%6,%7}, {%8,%9}, {%0,%1,%2,%3};"
                 : "+f"(c[0]), "+f"(c[1]), "+f"(c[2]), "+f"(c[3])
                 : "r"(a[0]), "r"(a[1]), "r"(a[2]), "r"(a[3]), "r"(b0), "r"(b1));
}
__device__ __forceinline__ unsigned long long ld_pkt(const unsigned long long* p) {
    unsigned long long v;
    asm volatile("ld.relaxed.gpu.global.u64 %0, [%1];" : "=l"(v) : "l"(p) : "memory");
    return v;
}
__device__ __forceinline__ void st_pkt(unsigned long long* p, uint32_t payload, uint32_t tag) {
    unsigned long long v = ((unsigned long long)tag << 32) | payload;
    asm volatile("st.relaxed.gpu.global.u64 [%0], %1;" ::"l"(p), "l"(v) : "memory");
}
__device__ __forceinline__ void ld_pkt2(const unsigned long long* p, unsigned long long& a, unsigned long long& b) {
    asm volatile("ld.relaxed.gpu.global.v2.u64 {%0,%1}, [%2];" : "=l"(a), "=l"(b) : "l"(p) : "memory");
}
__device__ __forceinline__ void st_pkt2(unsigned long long* p, uint32_t v0, uint32_t v1, uint32_t tag) {
    const unsigned long long a = ((unsigned long long)tag << 32) | v0, b = ((unsigned long long)tag << 32) | v1;
    asm volatile("st.relaxed.gpu.global.v2.u64 [%0], {%1,%2};" ::"l"(p), "l"(a), "l"(b) : "memory");
}
template <int N, int STRIDE>
__device__ __forceinline__ void poll_pkts(const unsigned long long* p, uint32_t (&out)[N], uint32_t tag) {
    uint32_t n = 0;
    while (true) {
        unsigned long long v[N];
#pragma unroll
        for (int i = 0; i < N; i++) v[i] = ld_pkt(p + i * STRIDE);
        uint32_t bad[2] = {0u, 0u};
#pragma unroll
        for (int i = 0; i < N; i++) { bad[i & 1] |= (uint32_t)(v[i] >> 32) ^ tag; out[i] = (uint32_t)v[i]; }
        if (__all_sync(0xffffffffu, (bad[0] | bad[1]) == 0)) break;
        if (++n > SPIN_LIMIT) __trap();
    }
}
template <int N, int STRIDE>
__device__ __forceinline__ void poll_pairs(const unsigned long long* p, uint32_t (&out)[2 * N], uint32_t tag) {
    uint32_t n = 0;
    while (true) {
        unsigned long long v[2 * N];
#pragma unroll
        for (int i = 0; i < N; i++) ld_pkt2(p + i * STRIDE, v[2 * i], v[2 * i + 1]);
        uint32_t bad[4] = {0u, 0u, 0u, 0u};
#pragma unroll
        for (int i = 0; i < 2 * N; i++) { bad[i & 3] |= (uint32_t)(v[i] >> 32) ^ tag; out[i] = (uint32_t)v[i]; }
        if (__all_sync(0xffffffffu, ((bad[0] | bad[1]) | (bad[2] | bad[3])) == 0)) break;
        if (++n > SPIN_LIMIT) __trap();
    }
}
__device__ __forceinline__ void spin_cycles(uint32_t n) { if (n) { const uint32_t t0 = (uint32_t)clock(); while ((uint32_t)clock() - t0 < n) { } } }
template <int N, int STRIDE>
__device__ __forceinline__ void poll_pairs_lazy(const unsigned long long* p, uint32_t (&out)[2 * N], uint32_t tag, int lane, uint32_t backoff) {
    uint32_t n = 0;
    while (true) {
        unsigned long long v[2 * N];
#pragma unroll
        for (int i = 0; i < N; i++) ld_pkt2(p + i * STRIDE, v[2 * i], v[2 * i + 1]);
        uint32_t bad = 0;
#pragma unroll
        for (int i = 0; i < 2 * N; i++) { bad |= (uint32_t)(v[i] >> 32) ^ tag; out[i] = (uint32_t)v[i]; }
        if (__all_sync(0xffffffffu, bad == 0)) break;
        if (backoff && lane == 0) {
            while ((uint32_t)(ld_pkt(p) >> 32) != tag) {
                __nanosleep(backoff);
                if (++n > SPIN_LIMIT) __trap();
            }
        }
        if (++n > SPIN_LIMIT) __trap();
        __syncwarp();
    }
}
__device__ __forceinline__ void wait_first(const unsigned long long* p, uint32_t tag, int lane, uint32_t backoff) {
    if (lane == 0) {
        uint32_t n = 0;
        while ((uint32_t)(ld_pkt(p) >> 32) != tag) {
            if (backoff) __nanosleep(backoff);
            if (++n > SPIN_LIMIT) __trap();
        }
    }
    __syncwarp();
}
__device__ __forceinline__ float ex2(float x) { float y; asm("ex2.approx.ftz.f32 %0, %1;" : "=f"(y) : "f"(x)); return y; }
__device__ __forceinline__ uint32_t pack_bf16(float lo, float hi) {
    __nv_bfloat162 v = __floats2bfloat162_rn(lo, hi);
    return *reinterpret_cast<uint32_t*>(&v);
}
__device__ __forceinline__ float bf_lo(uint32_t v) { return __uint_as_float(v << 16); }
__device__ __forceinline__ float bf_hi(uint32_t v) { return __uint_as_float(v & 0xffff0000u); }
__device__ __forceinline__ float bf16r(float x) { return bf_lo(pack_bf16(x, 0.f)); }
__device__ __forceinline__ float warp_sum(float v) {
#pragma unroll
    for (int o = 16; o > 0; o >>= 1) v += __shfl_xor_sync(0xffffffffu, v, o);
    return v;
}
__device__ __forceinline__ void sts32(uint32_t addr, uint32_t v) { asm volatile("st.shared.b32 [%0], %1;" ::"r"(addr), "r"(v) : "memory"); }
__device__ __forceinline__ void sts32f(uint32_t addr, float v) { asm volatile("st.shared.f32 [%0], %1;" ::"r"(addr), "f"(v) : "memory"); }
__device__ __forceinline__ uint32_t lds32(uint32_t addr) { uint32_t v; asm volatile("ld.volatile.shared.b32 %0, [%1];" : "=r"(v) : "r"(addr) : "memory"); return v; }
__device__ __forceinline__ float lds32f(uint32_t addr) { float v; asm volatile("ld.shared.f32 %0, [%1];" : "=f"(v) : "r"(addr) : "memory"); return v; }
__device__ __forceinline__ uint2 lds64(uint32_t addr) { uint2 v; asm volatile("ld.shared.v2.b32 {%0,%1}, [%2];" : "=r"(v.x), "=r"(v.y) : "r"(addr) : "memory"); return v; }
__device__ __forceinline__ uint4 lds128(uint32_t addr) { uint4 v; asm volatile("ld.shared.v4.b32 {%0,%1,%2,%3}, [%4];" : "=r"(v.x), "=r"(v.y), "=r"(v.z), "=r"(v.w) : "r"(addr) : "memory"); return v; }
__device__ __forceinline__ void sts64f(uint32_t addr, float a, float b) { asm volatile("st.shared.v2.f32 [%0], {%1,%2};" ::"r"(addr), "f"(a), "f"(b) : "memory"); }
__device__ __forceinline__ void sts128(uint32_t addr, uint4 v) { asm volatile("st.shared.v4.b32 [%0], {%1,%2,%3,%4};" ::"r"(addr), "r"(v.x), "r"(v.y), "r"(v.z), "r"(v.w) : "memory"); }
__device__ __forceinline__ uint32_t pin32(uint32_t v) { asm volatile("mov.b32 %0, %0;" : "+r"(v)); return v; }
__device__ __forceinline__ void sync_attn() { asm volatile("bar.sync 1, 256;" ::: "memory"); }
__device__ __forceinline__ void sync_comp() { asm volatile("bar.sync 2, 288;" ::: "memory"); }

__device__ __noinline__ float centred_variance(uint32_t x0, uint32_t x1, uint32_t x2, uint32_t x3, uint32_t x4, uint32_t x5, uint32_t x6,
                                               uint32_t x7, uint32_t x8, float mean) {
    const uint32_t xv[9] = {x0, x1, x2, x3, x4, x5, x6, x7, x8};
    float c = 0.f;
#pragma unroll
    for (int i = 0; i < 9; i++) { const float a = bf_lo(xv[i]) - mean, b = bf_hi(xv[i]) - mean; c = fmaf(a, a, fmaf(b, b, c)); }
    return warp_sum(c) * (1.0f / 576.0f);
}
__device__ __forceinline__ void layernorm_row(const uint32_t (&xv)[9], uint32_t dst_addr) {
    float s0 = 0.f, s1 = 0.f, q0 = 0.f, q1 = 0.f;
#pragma unroll
    for (int i = 0; i < 9; i++) {
        const float a = bf_lo(xv[i]), b = bf_hi(xv[i]);
        s0 += a; s1 += b; q0 = fmaf(a, a, q0); q1 = fmaf(b, b, q1);
    }
    float s = s0 + s1, q = q0 + q1;
#pragma unroll
    for (int o = 16; o > 0; o >>= 1) { s += __shfl_xor_sync(0xffffffffu, s, o); q += __shfl_xor_sync(0xffffffffu, q, o); }
    const float mean = s * (1.0f / 576.0f);
    float var = fmaf(-mean, mean, q * (1.0f / 576.0f));
    if (!(mean * mean <= 32.0f * var)) var = centred_variance(xv[0], xv[1], xv[2], xv[3], xv[4], xv[5], xv[6], xv[7], xv[8], mean);
    float den, rcp;
    asm("sqrt.approx.ftz.f32 %0, %1;" : "=f"(den) : "f"(bf16r(bf16r(var) + 1e-5f)));
    asm("rcp.approx.ftz.f32 %0, %1;" : "=f"(rcp) : "f"(bf16r(den)));
    const __nv_bfloat162 mb2 = __float2bfloat162_rn(mean);
#pragma unroll
    for (int i = 0; i < 9; i++) {
        __nv_bfloat162 d2 = __hsub2(*reinterpret_cast<const __nv_bfloat162*>(&xv[i]), mb2);
        const uint32_t du = *reinterpret_cast<uint32_t*>(&d2);
        sts32(dst_addr + 128 * i, pack_bf16(bf_lo(du) * rcp, bf_hi(du) * rcp));
    }
}

template <int KSTEPS, int PITCH>
__device__ __forceinline__ void load_wfrags(uint32_t (&wf)[KSTEPS * 2], uint32_t lane_addr) {
#pragma unroll
    for (int i = 0; i < KSTEPS / 2; i++) {
        uint32_t r[4];
        ldsm_x4_t(r, lane_addr + i * 32 * PITCH);
        wf[4 * i] = r[0]; wf[4 * i + 1] = r[1]; wf[4 * i + 2] = r[2]; wf[4 * i + 3] = r[3];
    }
}
template <int NP, int DEPTH>
__device__ __forceinline__ void gemm_tile(float& o0, float& o1, const uint32_t (&wf)[NP * 4], uint32_t a_lane, int npairs) {
    float c[4][4];
#pragma unroll
    for (int i = 0; i < 4; i++) { c[i][0] = c[i][1] = c[i][2] = c[i][3] = 0.f; }
    uint32_t r[DEPTH][4];
#pragma unroll
    for (int i = 0; i < DEPTH; i++) ldsm_x4(r[i], a_lane + i * 64);
#pragma unroll
    for (int i = 0; i < NP; i++) {
        if (i < NP - 1 || npairs == NP) {
            mma16816(c[(i & 1) * 2], r[i % DEPTH], wf[4 * i], wf[4 * i + 1]);
            mma16816(c[(i & 1) * 2 + 1], r[i % DEPTH], wf[4 * i + 2], wf[4 * i + 3]);
        }
        if (i + DEPTH < NP) ldsm_x4(r[i % DEPTH], a_lane + (i + DEPTH) * 64);
    }
    o0 = (c[0][0] + c[2][0]) + (c[1][2] + c[3][2]);
    o1 = (c[0][1] + c[2][1]) + (c[1][3] + c[3][3]);
}
template <int ACT_P>
__device__ __forceinline__ uint32_t act_lane_off(int lane) { return (lane & 7) * ACT_P + ((((lane >> 3) & 1) << 1) | (lane >> 4)) * 16; }

#define TS(i) do { } while (0)

__global__ void __launch_bounds__(NTHREADS, 1)
fused_decode_kernel(const __grid_constant__ Params p) {
    extern __shared__ __align__(1024) uint8_t smem_raw[];
    const uint32_t sb = smem_u32(smem_raw);
    const int tid = threadIdx.x, lane = tid & 31;
    const int warp = __shfl_sync(0xffffffffu, tid >> 5, 0);
    const int cta = blockIdx.x, g = cta >> 3, j = cta & 7;
    const uint32_t bars = sb + SM_BAR;

    if (warp == 9) {
        uint32_t leader;
        asm volatile("{\n.reg .pred p;\nelect.sync _|p, 0xffffffff;\nselp.u32 %0, 1, 0, p;\n}" : "=r"(leader));
        const uint32_t sb = pin32(smem_u32(smem_raw)), bars = sb + SM_BAR;
        if (leader) TS(0);
        const long long t_start = clock64();
        if (leader) {
#pragma unroll 1
            for (int b = 0; b < 25; b++) mbar_init(bars + b * 8, (b >= BAR_EMPTY && b < BAR_W) ? 8 : 1);
            sts32(sb + SM_WDYN, W_BULK); sts32(sb + SM_PROG, 0);
            if (sb & 1023u) __trap();
            asm volatile("fence.proxy.async.shared::cta;" ::: "memory");
        }
        __syncthreads();
        while (clock64() - t_start < K_DELAY) { }
        uint64_t stream_pol;
        asm volatile("createpolicy.fractional.L2::evict_first.b64 %0, 1.0;" : "=l"(stream_pol));
        int row = (j * 16 + g) * SK + (SK - WIN);
        uint32_t u = 0;
        uint32_t lu = 0, lpar = 0;
        int landed = 0;
        uint32_t es = 4, epar = 0;
#pragma unroll 1
        for (int i = 0; i < 64; i++) {
            const int w = i < B_BULK ? W_START : (int)lds32(sb + SM_WDYN);
#pragma unroll 1
            while (landed <= i - w) {
                mbar_wait(bars + (BAR_FULL + lu) * 8, lpar);
                landed++;
                if (++lu == 2 * NSLOT) { lu = 0; lpar ^= 1; }
            }
            if (i >= 8 && (i & 1) == 0) {
                mbar_wait(bars + (BAR_EMPTY + es) * 8, epar);
                if (++es == NSLOT) es = 0;
                if (es == 4) epar ^= 1;
            }
            if (leader) {
                const CUtensorMap* tm = i < 32 ? &p.tmK : &p.tmV;
                const uint32_t bar = bars + (BAR_FULL + u) * 8;
                const uint32_t dst = sb + (u >> 1) * TILE_BYTES + (u & 1) * (TILE_BYTES / 4);
                mbar_expect_tx(bar, TILE_BYTES / 2);
                tma2d_hint(dst, tm, 0, row, bar, stream_pol);
                tma2d_hint(dst + TILE_BYTES / 2, tm, 64, row, bar, stream_pol);
                asm volatile("red.relaxed.gpu.global.add.u32 [%0], 1;" ::"l"(p.epoch + 8) : "memory");
                sts32(sb + SM_PROG, i + 1);
                if ((i & 1) == 0) TS(2 + (i >> 1));
            }
            row += i == 31 ? TILE_KEYS / 2 - WIN : TILE_KEYS / 2;
            if (++u == 2 * NSLOT) u = 0;
        }
#pragma unroll 1
        for (int k = 0; k < 7; k++) {
            if (k >= W_END) mbar_wait(bars + (BAR_W + k - W_END) * 8, 0);
            else {
#pragma unroll 1
                while (landed <= 64 + k - W_END) {
                    mbar_wait(bars + (BAR_FULL + lu) * 8, lpar);
                    landed++;
                    if (++lu == 2 * NSLOT) { lu = 0; lpar ^= 1; }
                }
            }
            if ((0x2b >> k) & 1) {
                mbar_wait(bars + (BAR_EMPTY + es) * 8, epar);
                if (++es == NSLOT) es = 0;
                if (es == 4) epar ^= 1;
            }
            if (leader) {
                const bool is1 = k >= 2 && k < 5;
                const CUtensorMap* tm = &p.tmWo + (k < 2 ? 0 : (is1 ? 1 : 2));
                const int4 it = p.witem[k];
                mbar_expect_tx(bars + (BAR_W + k) * 8, it.y);
                tma2d(sb + it.x, tm, is1 ? (g * 288 + j * 36) & ~7 : j * 72, g * it.z + it.w, bars + (BAR_W + k) * 8);
                TS(40 + k);
            }
        }
        return;
    }

    const int g8 = lane >> 2, t4 = lane & 3;
    unsigned long long* const scratch = p.scratch;
    const bool is_attn = warp < 8;
    const bool is_red = (warp == 8) && (g < 9);
    uint32_t hv[9];
    uint32_t res = 0;
    if (is_attn) {
        const uint32_t* xr = reinterpret_cast<const uint32_t*>(p.x + warp * D_MODEL) + lane;
#pragma unroll
        for (int i = 0; i < 9; i++) hv[i] = __ldg(xr + 32 * i);
    } else if (is_red) {
        res = __ldg(reinterpret_cast<const uint32_t*>(p.x + g8 * D_MODEL + j * 72 + g * 8) + t4);
    }
    if (is_attn) {
        const __nv_bfloat16* src = p.wq + (tid >> 2) * 4096 + g * 256 + j * 32 + (tid & 3) * 8;
        uint32_t dst = sb + WQ_OFF + (tid >> 2) * 80 + (tid & 3) * 16;
#pragma unroll 1
        for (int i = 0; i < 9; i++) {
            asm volatile("cp.async.cg.shared.global [%0], [%1], 16;" ::"r"(dst), "l"(src) : "memory");
            src += 64 * 4096; dst += 64 * 80;
        }
        asm volatile("cp.async.commit_group;" ::: "memory");
    }
    uint32_t tag;
    asm volatile("ld.relaxed.gpu.global.u32 %0, [%1];" : "=r"(tag) : "l"(p.epoch) : "memory");
    const uint32_t q_out = QLL_OFF + (g * 8 + g8) * 128 + j * 16 + warp * 4 + t4;
    const uint32_t o_out = pin32(OLL_OFF + cta * 128 + ((lane >> 3) & 1) * 64 + warp * 8 + ((lane >> 2) & 1) * 4 + (lane & 3));
    const uint32_t part_out = pin32(HLL_OFF + ((warp * 8 + j) * 16 + g) * 64 + lane * 2);
    const int a_col = warp * 8 + 2 * t4 - (j & 1) * 4;
    const bool a_valid = warp < 5 && a_col >= 0 && a_col < 36;
    const uint32_t x_out = pin32(is_attn ? ALL_OFF + (g * 8 + g8) * 144 + j * 18 + (a_col >> 1) : HB_OFF + g8 * 288 + j * 36 + g * 4 + t4);
    const uint32_t x_in = pin32(HB_OFF + (cta % HB_COPIES) * 2304 + warp * 288 + lane);
    const uint32_t red_in = pin32(HLL_OFF + cta * 1024 + warp * 128 + lane * 2);
    const uint32_t ln_dst = pin32(sb + SM_ACT + warp * ACT_PITCH * 2 + lane * 4);
    const uint32_t gat_dst_a = pin32(sb + SM_GAT + (tid / 36) * (A_PITCH * 2) + (tid % 36) * 16);
    if (warp < 4) st_pkt(scratch + q_out, 0u, 0u);
    tag += 1;
    __syncthreads();
    TS(0);

#pragma unroll 1
    for (int ph = 0; ph < 2; ph++) {
        float o0, o1;
        if (is_attn) {
            uint32_t wf[72];
            if (ph == 0) {
                asm volatile("cp.async.wait_group 0;" ::: "memory");
                sync_attn();
            }
            if (warp < 5) {
                if (ph) mbar_wait_n<3>(bars + (BAR_W + 2) * 8);
                TS(2 + 10 * ph);
                load_wfrags<36, 80>(wf, sb + (ph ? W1_OFF : WQ_OFF) + lane * 80 + warp * 16);
                if (ph == 0) {
                    __syncwarp();
                    if (lane < (warp < 3 ? 2 : 1)) { mbar_arrive(bars + (BAR_EMPTY + 4) * 8); mbar_arrive(bars + (BAR_EMPTY + 5) * 8); }
                }
            }
            if (ph) {
                spin_cycles(H_DELAY);
                wait_first(scratch + x_in + 256, tag, lane, H_BACKOFF);
                TS(25);
                poll_pkts<9, 32>(scratch + x_in, hv, tag);
                TS(10);
            }
            layernorm_row(hv, ln_dst);
            sync_attn();
            TS(1 + 10 * ph);
            if (warp < 5) {
                gemm_tile<18, 6>(o0, o1, wf, sb + SM_ACT + act_lane_off<ACT_PITCH * 2>(lane), 18);
                uint32_t f = pack_bf16(o0, o1);
                if (ph) f = pack_bf16(fmaxf(bf_lo(f), 0.f), fmaxf(bf_hi(f), 0.f));
                if (ph ? a_valid : (warp < 4)) st_pkt(scratch + (ph ? x_out : q_out), f, tag);
            }
            TS(ph ? 13 : 20);
            if (ph == 0) {
                if (tid < 128) {
                    uint32_t v[1];
                    poll_pkts<1, 1>(scratch + QLL_OFF + cta * 128 + tid, v, tag);
                    TS(21);
                    sts32(sb + SM_QS + ((tid & 64) + (tid & 3) * 16 + ((tid & 63) >> 2)) * 4, v[0]);
                }
                sync_attn();
                TS(3);
                uint32_t qf[16];
#pragma unroll
                for (int s = 0; s < 4; s++) {
                    const uint4 v = lds128(sb + SM_QS + ((g8 & 1) * 64 + t4 * 16) * 4 + s * 16);
                    qf[4 * s] = v.x; qf[4 * s + 1] = v.y; qf[4 * s + 2] = v.z; qf[4 * s + 3] = v.w;
                }

                float m0 = -INFINITY, m1 = -INFINITY;
                {
                    const int krow = warp * 16 + (lane & 7) + ((lane >> 3) & 1) * 8;
                    const uint32_t rowoff = krow * 128;
                    const uint32_t chi = lane >> 4;
                    const uint32_t sw = krow & 7;
                    uint32_t slot = 0, par = 0;
                    uint32_t wsc = sb + SM_SC + ((warp >> 1) * 40 + (warp & 1) * 16 + g8) * 4;
#pragma unroll 1
                    for (int n = 0; n < NTILE; n++) {
                        mbar_wait(bars + (BAR_FULL + 2 * slot + (warp >> 2)) * 8, par);
                        const uint32_t base = sb + slot * TILE_BYTES + rowoff;
                        float c0[4] = {0.f, 0.f, 0.f, 0.f}, c1[4] = {0.f, 0.f, 0.f, 0.f};
#pragma unroll
                        for (int s = 0; s < 8; s += 2) {
                            uint32_t a[4], b[4];
                            ldsm_x4(a, base + (s >> 2) * (TILE_BYTES / 2) + ((((s & 3) * 2 + chi) ^ sw) << 4));
                            ldsm_x4(b, base + (s >> 2) * (TILE_BYTES / 2) + ((((s & 3) * 2 + 2 + chi) ^ sw) << 4));
                            mma16816(c0, a, qf[2 * s], qf[2 * s + 1]);
                            mma16816(c1, b, qf[2 * s + 2], qf[2 * s + 3]);
                        }
                        __syncwarp();
                        if (lane == 0) mbar_arrive(bars + (BAR_EMPTY + slot) * 8);
                        const float scale = 0.08838834764831845f;
                        const uint32_t u0 = pack_bf16(c0[0] + c1[0], c0[1] + c1[1]), u1 = pack_bf16(c0[2] + c1[2], c0[3] + c1[3]);
                        const uint32_t s0 = pack_bf16(bf_lo(u0) * scale, bf_hi(u0) * scale), s1 = pack_bf16(bf_lo(u1) * scale, bf_hi(u1) * scale);
                        m0 = fmaxf(m0, fmaxf(bf_lo(s0), bf_lo(s1)));
                        m1 = fmaxf(m1, fmaxf(bf_hi(s0), bf_hi(s1)));
                        if (t4 == 0) { sts32(wsc, s0); sts32(wsc + 32, s1); }
                        wsc += 4 * 40 * 4;
                        if (++slot == NSLOT) { slot = 0; par ^= 1; }
                    }
                }
                TS(4);
                {
#pragma unroll
                    for (int o = 16; o > 2; o >>= 1) { m0 = fmaxf(m0, __shfl_xor_sync(0xffffffffu, m0, o)); m1 = fmaxf(m1, __shfl_xor_sync(0xffffffffu, m1, o)); }
                    if (lane == 0) { sts32f(sb + SM_RED + warp * 4, m0); sts32f(sb + SM_RED + 32 + warp * 4, m1); }
                    sync_attn();
                    uint2 sv[4];
#pragma unroll
                    for (int i = 0; i < 4; i++) sv[i] = lds64(sb + SM_SC + ((tid >> 2) * 40 + 2 * t4 + 8 * i) * 4);
                    sync_attn();
#pragma unroll 1
                    for (int h = 0; h < 2; h++) {
                        const uint4 a = lds128(sb + SM_RED + h * 32), b = lds128(sb + SM_RED + h * 32 + 16);
                        const float m = fmaxf(fmaxf(fmaxf(__uint_as_float(a.x), __uint_as_float(a.y)), fmaxf(__uint_as_float(a.z), __uint_as_float(a.w))),
                                              fmaxf(fmaxf(__uint_as_float(b.x), __uint_as_float(b.y)), fmaxf(__uint_as_float(b.z), __uint_as_float(b.w))));
                        const uint32_t sel = h ? 0x3244u : 0x1044u;
                        const float l2e = 1.4426950408889634f, ml = -m * l2e;
                        float e[8], sum = 0.f;
#pragma unroll
                        for (int i = 0; i < 4; i++) {
                            e[2 * i] = ex2(fmaf(__uint_as_float(__byte_perm(sv[i].x, 0u, sel)), l2e, ml));
                            e[2 * i + 1] = ex2(fmaf(__uint_as_float(__byte_perm(sv[i].y, 0u, sel)), l2e, ml));
                            sum += e[2 * i] + e[2 * i + 1];
                        }
                        sum = warp_sum(sum);
                        if (lane == 0) sts32f(sb + SM_RED + 64 + h * 32 + warp * 4, sum);
                        sync_attn();
                        const uint4 c = lds128(sb + SM_RED + 64 + h * 32), d = lds128(sb + SM_RED + 80 + h * 32);
                        const float tot = ((__uint_as_float(c.x) + __uint_as_float(c.y)) + (__uint_as_float(c.z) + __uint_as_float(c.w))) +
                                          ((__uint_as_float(d.x) + __uint_as_float(d.y)) + (__uint_as_float(d.z) + __uint_as_float(d.w)));
                        const float inv = __fdividef(1.0f, tot);
                        sts128(sb + SM_SC + h * P_HEAD_STRIDE + tid * 16, make_uint4(pack_bf16(e[0] * inv, e[1] * inv), pack_bf16(e[2] * inv, e[3] * inv),
                                                                                     pack_bf16(e[4] * inv, e[5] * inv), pack_bf16(e[6] * inv, e[7] * inv)));
                    }
                    sync_attn();
                }
                TS(5);
                float c0[4] = {0.f, 0.f, 0.f, 0.f}, c1[4] = {0.f, 0.f, 0.f, 0.f};
                {
                    const int krow = (lane & 7) + (lane >> 4) * 8;
                    const uint32_t chunk = (warp & 3) * 2 + ((lane >> 3) & 1);
                    const uint32_t lane_off = (warp >> 2) * (TILE_BYTES / 2) + krow * 128 + ((chunk ^ (lane & 7)) << 4);
                    uint32_t pb = sb + SM_SC + (g8 & 1) * P_HEAD_STRIDE + t4 * 16;
                    uint32_t slot = NTILE % NSLOT, par = (NTILE / NSLOT) & 1;
#pragma unroll 1
                    for (int n = NTILE; n < 2 * NTILE; n++) {
                        const uint32_t base = sb + slot * TILE_BYTES + lane_off;
#pragma unroll
                        for (int s = 0; s < 8; s += 2) {
                            if ((s & 3) == 0) mbar_wait(bars + (BAR_FULL + 2 * slot + (s >> 2)) * 8, par);
                            uint32_t a[4], b[4];
                            const uint4 pv = lds128(pb + (s >> 1) * 64);
                            ldsm_x4_t(a, base + s * 2048);
                            ldsm_x4_t(b, base + (s + 1) * 2048);
                            mma16816(c0, a, pv.x, pv.y);
                            mma16816(c1, b, pv.z, pv.w);
                        }
                        __syncwarp();
                        if (lane == 0) mbar_arrive(bars + (BAR_EMPTY + slot) * 8);
                        pb += 256;
                        if (++slot == NSLOT) { slot = 0; par ^= 1; }
                        if (n == PREWRITE_TILE) {
                            if (lane < 16) st_pkt(scratch + o_out, 0u, 0u);
                            st_pkt2(scratch + part_out, 0u, 0u, 0u); st_pkt2(scratch + part_out + (YLL_OFF - HLL_OFF), 0u, 0u, 0u);
                            if (a_valid) st_pkt(scratch + x_out, 0u, 0u);
                            if (warp == 0) asm volatile("bar.arrive 3, 64;" ::: "memory");
                        }
                    }
                }
                TS(6);
                const uint32_t pa = pack_bf16(c0[0] + c1[0], c0[1] + c1[1]);
                const uint32_t pb2 = pack_bf16(c0[2] + c1[2], c0[3] + c1[3]);
                const int src = (lane & 3) * 8;
                const uint32_t a0 = __shfl_sync(0xffffffffu, pa, src), a1 = __shfl_sync(0xffffffffu, pa, src + 4);
                const uint32_t b0 = __shfl_sync(0xffffffffu, pb2, src), b1 = __shfl_sync(0xffffffffu, pb2, src + 4);
                const uint32_t lo = (lane & 4) ? b0 : a0, hi = (lane & 4) ? b1 : a1;
                if (lane < 16) st_pkt(scratch + o_out, __byte_perm(lo, hi, (lane & 8) ? 0x7632 : 0x5410), tag);
                TS(22);
            }
        } else if (ph == 0) {
            if (lane == 0) {
                const uint32_t base = (tag - 1) * (NCTA * 64);
                uint32_t own, n = 0;
                do {
                    uint32_t tot;
                    asm volatile("ld.relaxed.gpu.global.u32 %0, [%1];" : "=r"(tot) : "l"(p.epoch + 8) : "memory");
                    own = lds32(sb + SM_PROG);
                    const int lead = (int)(own * NCTA) - (int)(tot - base);
                    int w = W_BULK - (lead * BAL_GAIN + (lead >= 0 ? 64 * 16 : -64 * 16)) / (NCTA * 16);
                    w = w < W_MIN ? W_MIN : (w > W_MAX ? W_MAX : w);
                    asm volatile("st.volatile.shared.b32 [%0], %1;" ::"r"(sb + SM_WDYN), "r"(w) : "memory");
                    __nanosleep(BAL_SLEEP);
                } while (own < 60 && ++n < 100000);
            }
            __syncwarp();
            asm volatile("bar.sync 3, 64;" ::: "memory");
            st_pkt2(scratch + part_out, 0u, 0u, 0u); st_pkt2(scratch + part_out + (YLL_OFF - HLL_OFF), 0u, 0u, 0u);
            if (is_red) {
#pragma unroll
                for (int r = 0; r < HB_COPIES; r++) st_pkt(scratch + x_out + r * 2304, 0u, 0u);
            }
        }

        {
            uint32_t wf[36];
            mbar_wait_n<2>(bars + (BAR_W + 5 * ph) * 8);
            TS(8 + 7 * ph);
            load_wfrags<18, 144>(wf, sb + (ph ? W2_OFF : WO_OFF) + lane * 144 + warp * 16);
            if (ph || is_attn) {
                uint32_t v[4];
                const unsigned long long* src = scratch + ((ph ? ALL_OFF + g * 1152 : OLL_OFF + g * 1024) + tid * 4);
                if (ph == 0) wait_first(src, tag, lane, BACKOFF_NS);
                TS(23 + ph);
                if (ph) spin_cycles(A_DELAY);
                poll_pairs<2, 2>(src, v, tag);
                sts128(ph ? gat_dst_a : sb + SM_GAT + warp * (A_PITCH * 2) + lane * 16, make_uint4(v[0], v[1], v[2], v[3]));
            }
            sync_comp();
            TS(7 + 7 * ph);
            gemm_tile<9, 9>(o0, o1, wf, sb + SM_GAT + act_lane_off<A_PITCH * 2>(lane), ph ? 9 : 8);
            st_pkt2(scratch + (part_out + (ph ? YLL_OFF - HLL_OFF : 0)), __float_as_uint(o0), __float_as_uint(o1), tag);
            TS(9 + 7 * ph);
        }
        if (g < 9) {
            if (is_attn) {
                uint32_t v[4];
                spin_cycles(ph ? RED_DELAY : RED_DELAY0);
                poll_pairs_lazy<2, 64>(scratch + (red_in + (ph ? YLL_OFF - HLL_OFF : 0)), v, tag, lane, ph ? R1_BACKOFF : R0_BACKOFF);
                sts64f(sb + SM_SC + tid * 8, __uint_as_float(v[0]) + __uint_as_float(v[2]), __uint_as_float(v[1]) + __uint_as_float(v[3]));
            }
            TS(26 + ph);
            sync_comp();
            if (!is_attn) {
                float a[8], b[8];
#pragma unroll
                for (int w = 0; w < 8; w++) { const uint2 v = lds64(sb + SM_SC + w * 256 + lane * 8); a[w] = __uint_as_float(v.x); b[w] = __uint_as_float(v.y); }
                const float s0 = ((a[0] + a[1]) + (a[2] + a[3])) + ((a[4] + a[5]) + (a[6] + a[7]));
                const float s1 = ((b[0] + b[1]) + (b[2] + b[3])) + ((b[4] + b[5]) + (b[6] + b[7]));
                res = pack_bf16(bf_lo(res) + bf16r(s0), bf_hi(res) + bf16r(s1));
                if (ph == 0) {
#pragma unroll
                    for (int r = 0; r < HB_COPIES; r++) st_pkt(scratch + x_out + r * 2304, res, tag);
                    TS(10);
                } else {
                    *reinterpret_cast<uint32_t*>(p.out + g8 * D_MODEL + j * 72 + g * 8 + 2 * t4) = res;
                    TS(17);
                    if (cta == 0 && lane == 0) asm volatile("st.relaxed.gpu.global.u32 [%0], %1;" ::"l"(p.epoch), "r"(tag) : "memory");
                }
            }
        }
    }
}

typedef CUresult (*EncodeTiledFn)(CUtensorMap*, CUtensorMapDataType, cuuint32_t, void*, const cuuint64_t*, const cuuint64_t*,
                                  const cuuint32_t*, const cuuint32_t*, CUtensorMapInterleave, CUtensorMapSwizzle,
                                  CUtensorMapL2promotion, CUtensorMapFloatOOBfill);

#define PROMO_W CU_TENSOR_MAP_L2_PROMOTION_L2_128B
#define PROMO_KV CU_TENSOR_MAP_L2_PROMOTION_L2_256B
void make_map(EncodeTiledFn enc, CUtensorMap* tm, const void* ptr, uint64_t cols, uint64_t rows, uint32_t box_cols, uint32_t box_rows,
              CUtensorMapSwizzle sw) {
    cuuint64_t gd[2] = {cols, rows};
    cuuint64_t gs[1] = {cols * 2};
    cuuint32_t bd[2] = {box_cols, box_rows};
    cuuint32_t es[2] = {1, 1};
    enc(tm, CU_TENSOR_MAP_DATA_TYPE_BFLOAT16, 2, const_cast<void*>(ptr), gd, gs, bd, es, CU_TENSOR_MAP_INTERLEAVE_NONE, sw,
        sw == CU_TENSOR_MAP_SWIZZLE_NONE ? PROMO_W : PROMO_KV, CU_TENSOR_MAP_FLOAT_OOB_FILL_NONE);
}

}

extern "C" void kernel_launch(void* const* d_in, const int* in_sizes, int n_in, void* d_out, int out_size) {
    (void)in_sizes; (void)n_in; (void)out_size;
    static EncodeTiledFn enc = nullptr;
    static unsigned long long* scratch = nullptr;
    static unsigned int* epoch = nullptr;
    if (!enc) {
        cudaDriverEntryPointQueryResult qr;
        void* fn = nullptr;
        cudaGetDriverEntryPoint("cuTensorMapEncodeTiled", &fn, cudaEnableDefault, &qr);
        enc = (EncodeTiledFn)fn;
        cudaFuncSetAttribute(fused_decode_kernel, cudaFuncAttributeMaxDynamicSharedMemorySize, SMEM_BYTES);
        cudaGetSymbolAddress((void**)&scratch, g_scratch);
        cudaGetSymbolAddress((void**)&epoch, g_epoch);
    }
    Params p;
    make_map(enc, &p.tmK, d_in[1], 128, 8ull * 16 * SK, 64, TILE_KEYS / 2, CU_TENSOR_MAP_SWIZZLE_128B);
    make_map(enc, &p.tmV, d_in[2], 128, 8ull * 16 * SK, 64, TILE_KEYS / 2, CU_TENSOR_MAP_SWIZZLE_128B);
    make_map(enc, &p.tmWo, d_in[4], 576, 4096, 72, 128, CU_TENSOR_MAP_SWIZZLE_NONE);
    make_map(enc, &p.tmW1, d_in[6], 4608, 576, 40, 192, CU_TENSOR_MAP_SWIZZLE_NONE);
    make_map(enc, &p.tmW2, d_in[7], 576, 4608, 72, 144, CU_TENSOR_MAP_SWIZZLE_NONE);
    for (int k = 0; k < 7; k++) {
        if (k < 2) p.witem[k] = make_int4(WO_OFF + k * 128 * 144, 128 * 144, 256, k * 128);
        else if (k < 5) p.witem[k] = make_int4(W1_OFF + (k - 2) * 192 * 80, 192 * 80, 0, (k - 2) * 192);
        else p.witem[k] = make_int4(W2_OFF + (k - 5) * 144 * 144, 144 * 144, 288, (k - 5) * 144);
    }
    p.x = (const __nv_bfloat16*)d_in[0];
    p.wq = (const __nv_bfloat16*)d_in[3];
    p.out = (__nv_bfloat16*)d_out;
    p.scratch = scratch;
    p.epoch = epoch;
    fused_decode_kernel<<<NCTA, NTHREADS, SMEM_BYTES, cudaStreamPerThread>>>(p);
}
```

```cpp
#include <cuda_runtime.h>
#include <cuda_bf16.h>
#include <cuda.h>
#include <stdint.h>

namespace {

constexpr int D_MODEL = 576;
constexpr int NCTA = 128;
constexpr int NTHREADS = 320;
constexpr int SK = 8192;
constexpr int WIN = 2048;
constexpr int TILE_KEYS = 128;
constexpr int TILE_BYTES = TILE_KEYS * 256;
constexpr int NSLOT = 6;
constexpr int NTILE = WIN / TILE_KEYS;

constexpr int W_START = 4;
constexpr int B_BULK = 8;
constexpr int W_BULK = 4, W_MIN = 3, W_MAX = 8;
constexpr int BAL_GAIN = 16;
constexpr int BAL_SLEEP = 200;
constexpr int W_WO = 4;
constexpr int W_END = 2;
constexpr int HOLD_K = 5;
constexpr int K_DELAY = 2000;
constexpr int PREWRITE_TILE = 30;
constexpr int HB_COPIES = 4;
constexpr int O_BACKOFF = 100, H_BACKOFF = 50;
constexpr int RED_DELAY0 = 800, RED_DELAY1 = 200, A_DELAY = 100;

constexpr int SM_SC = NSLOT * TILE_BYTES;
constexpr int SM_ACT = SM_SC + 10240;
constexpr int ACT_PITCH = 584;
constexpr int SM_GAT = SM_ACT + 8 * ACT_PITCH * 2;
constexpr int A_PITCH = 296;
constexpr int SM_QS = SM_GAT + 8 * A_PITCH * 2;
constexpr int SM_RED = SM_QS + 512;
constexpr int SM_WDYN = SM_RED + 192, SM_PROG = SM_RED + 196;
constexpr int SM_BAR = SM_RED + 256;
constexpr int SM_TOTAL = SM_BAR + 256;
constexpr int SMEM_BYTES = SM_TOTAL;

constexpr int WQ_OFF = 4 * TILE_BYTES;
constexpr int WO_OFF = 2 * TILE_BYTES;
constexpr int WO_BYTES = 256 * 144;
constexpr int W1_OFF = WO_OFF + WO_BYTES;
constexpr int W1_BYTES = 576 * 80;
constexpr int W2_OFF = W1_OFF + W1_BYTES;
constexpr int W2_BYTES = 288 * 144;
constexpr int P_HEAD_STRIDE = 4096 + 64;
static_assert(W2_OFF + W2_BYTES <= NSLOT * TILE_BYTES, "weights do not fit");

constexpr int BAR_FULL = 0, BAR_EMPTY = 12, BAR_W = 18, BAR_GO = 25;

constexpr int QLL_OFF = 0;
constexpr int OLL_OFF = QLL_OFF + 16 * 8 * 128;
constexpr int HLL_OFF = OLL_OFF + 16 * 8 * 128;
constexpr int HB_OFF = HLL_OFF + 72 * 16 * 64;
constexpr int ALL_OFF = HB_OFF + HB_COPIES * 2304;
constexpr int YLL_OFF = ALL_OFF + 16 * 8 * 144;
constexpr int SCRATCH_U64 = YLL_OFF + 72 * 16 * 64;

struct __align__(64) Params {
    CUtensorMap tmK, tmV, tmWo, tmW1, tmW2;
    const __nv_bfloat16* x;
    const __nv_bfloat16* wq;
    __nv_bfloat16* out;
    unsigned long long* scratch;
    unsigned int* epoch;
    int4 witem[7];
};

__device__ unsigned long long g_scratch[SCRATCH_U64];
__device__ unsigned int g_epoch[32];

__device__ __forceinline__ uint32_t smem_u32(const void* p) { return (uint32_t)__cvta_generic_to_shared(p); }
__device__ __forceinline__ void mbar_init(uint32_t bar, uint32_t cnt) {
    asm volatile("mbarrier.init.shared::cta.b64 [%0], %1;" ::"r"(bar), "r"(cnt) : "memory");
}
__device__ __forceinline__ void mbar_expect_tx(uint32_t bar, uint32_t bytes) {
    asm volatile("mbarrier.arrive.expect_tx.shared::cta.b64 _, [%0], %1;" ::"r"(bar), "r"(bytes) : "memory");
}
__device__ __forceinline__ void mbar_arrive(uint32_t bar) {
    asm volatile("mbarrier.arrive.shared::cta.b64 _, [%0];" ::"r"(bar) : "memory");
}
__device__ __forceinline__ bool mbar_try(uint32_t bar, uint32_t parity) {
    uint32_t ok;
    asm volatile("{\n.reg .pred p;\nmbarrier.try_wait.parity.shared::cta.b64 p, [%1], %2;\nselp.u32 %0, 1, 0, p;\n}"
                 : "=r"(ok) : "r"(bar), "r"(parity) : "memory");
    return ok != 0;
}
constexpr uint32_t SPIN_LIMIT = 1u << 24;
__device__ __forceinline__ void mbar_wait(uint32_t bar, uint32_t parity) {
    asm volatile("{\n.reg .pred p;\n.reg .u32 n;\nmov.u32 n, 0;\n"
                 "MBW_LOOP:\nmbarrier.try_wait.parity.shared::cta.b64 p, [%0], %1;\n@p bra MBW_DONE;\n"
                 "add.u32 n, n, 1;\nsetp.lt.u32 p, n, 16777216;\n@p bra MBW_LOOP;\ntrap;\nMBW_DONE:\n}"
                 ::"r"(bar), "r"(parity) : "memory");
}
template <int N>
__device__ __forceinline__ void mbar_wait_n(uint32_t bar) {
    uint32_t n = 0;
    while (true) {
        bool ok = true;
#pragma unroll
        for (int i = 0; i < N; i++) ok = mbar_try(bar + i * 8, 0) & ok;
        if (ok) break;
        if (++n > SPIN_LIMIT) __trap();
    }
}
__device__ __forceinline__ void tma2d(uint32_t dst, const CUtensorMap* tm, int c0, int c1, uint32_t bar) {
    asm volatile("cp.async.bulk.tensor.2d.shared::cluster.global.mbarrier::complete_tx::bytes [%0], [%1, {%3, %4}], [%2];"
                 ::"r"(dst), "l"(tm), "r"(bar), "r"(c0), "r"(c1) : "memory");
}
__device__ __forceinline__ void tma2d_hint(uint32_t dst, const CUtensorMap* tm, int c0, int c1, uint32_t bar, uint64_t pol) {
    asm volatile("cp.async.bulk.tensor.2d.shared::cluster.global.mbarrier::complete_tx::bytes.L2::cache_hint [%0], [%1, {%3, %4}], [%2], %5;"
                 ::"r"(dst), "l"(tm), "r"(bar), "r"(c0), "r"(c1), "l"(pol) : "memory");
}
__device__ __forceinline__ void ldsm_x4(uint32_t (&r)[4], uint32_t addr) {
    asm volatile("ldmatrix.sync.aligned.m8n8.x4.shared.b16 {%0,%1,%2,%3}, [%4];"
                 : "=r"(r[0]), "=r"(r[1]), "=r"(r[2]), "=r"(r[3]) : "r"(addr) : "memory");
}
__device__ __forceinline__ void ldsm_x4_t(uint32_t (&r)[4], uint32_t addr) {
    asm volatile("ldmatrix.sync.aligned.m8n8.x4.trans.shared.b16 {%0,%1,%2,%3}, [%4];"
                 : "=r"(r[0]), "=r"(r[1]), "=r"(r[2]), "=r"(r[3]) : "r"(addr) : "memory");
}
__device__ __forceinline__ void mma16816(float (&c)[4], const uint32_t (&a)[4], uint32_t b0, uint32_t b1) {
    asm volatile("mma.sync.aligned.m16n8k16.row.col.f32.bf16.bf16.f32 {%0,%1,%2,%3}, {%4,%5,%6,%7}, {%8,%9}, {%0,%1,%2,%3};"
                 : "+f"(c[0]), "+f"(c[1]), "+f"(c[2]), "+f"(c[3])
                 : "r"(a[0]), "r"(a[1]), "r"(a[2]), "r"(a[3]), "r"(b0), "r"(b1));
}
__device__ __forceinline__ unsigned long long ld_pkt(const unsigned long long* p) {
    unsigned long long v;
    asm volatile("ld.relaxed.gpu.global.u64 %0, [%1];" : "=l"(v) : "l"(p) : "memory");
    return v;
}
__device__ __forceinline__ void st_pkt(unsigned long long* p, uint32_t payload, uint32_t tag) {
    unsigned long long v = ((unsigned long long)tag << 32) | payload;
    asm volatile("st.relaxed.gpu.global.u64 [%0], %1;" ::"l"(p), "l"(v) : "memory");
}
__device__ __forceinline__ void ld_pkt2(const unsigned long long* p, unsigned long long& a, unsigned long long& b) {
    asm volatile("ld.relaxed.gpu.global.v2.u64 {%0,%1}, [%2];" : "=l"(a), "=l"(b) : "l"(p) : "memory");
}
__device__ __forceinline__ void st_pkt2(unsigned long long* p, uint32_t v0, uint32_t v1, uint32_t tag) {
    const unsigned long long a = ((unsigned long long)tag << 32) | v0, b = ((unsigned long long)tag << 32) | v1;
    asm volatile("st.relaxed.gpu.global.v2.u64 [%0], {%1,%2};" ::"l"(p), "l"(a), "l"(b) : "memory");
}
template <int N, int STRIDE>
__device__ __forceinline__ void poll_pkts(const unsigned long long* p, uint32_t (&out)[N], uint32_t tag) {
    uint32_t n = 0;
    while (true) {
        unsigned long long v[N];
#pragma unroll
        for (int i = 0; i < N; i++) v[i] = ld_pkt(p + i * STRIDE);
        uint32_t bad[2] = {0u, 0u};
#pragma unroll
        for (int i = 0; i < N; i++) { bad[i & 1] |= (uint32_t)(v[i] >> 32) ^ tag; out[i] = (uint32_t)v[i]; }
        if (__all_sync(0xffffffffu, (bad[0] | bad[1]) == 0)) break;
        if (++n > SPIN_LIMIT) __trap();
    }
}
template <int N, int STRIDE>
__device__ __forceinline__ void poll_pairs(const unsigned long long* p, uint32_t (&out)[2 * N], uint32_t tag) {
    uint32_t n = 0;
    while (true) {
        unsigned long long v[2 * N];
#pragma unroll
        for (int i = 0; i < N; i++) ld_pkt2(p + i * STRIDE, v[2 * i], v[2 * i + 1]);
        uint32_t bad[4] = {0u, 0u, 0u, 0u};
#pragma unroll
        for (int i = 0; i < 2 * N; i++) { bad[i & 3] |= (uint32_t)(v[i] >> 32) ^ tag; out[i] = (uint32_t)v[i]; }
        if (__all_sync(0xffffffffu, ((bad[0] | bad[1]) | (bad[2] | bad[3])) == 0)) break;
        if (++n > SPIN_LIMIT) __trap();
    }
}
__device__ __forceinline__ void spin_cycles(uint32_t n) { if (n) { const uint32_t t0 = (uint32_t)clock(); while ((uint32_t)clock() - t0 < n) { } } }
__device__ __forceinline__ void wait_first(const unsigned long long* p, uint32_t tag, int lane, uint32_t backoff) {
    if (lane == 0) {
        uint32_t n = 0;
        while ((uint32_t)(ld_pkt(p) >> 32) != tag) {
            if (backoff) __nanosleep(backoff);
            if (++n > SPIN_LIMIT) __trap();
        }
    }
    __syncwarp();
}
__device__ __forceinline__ float ex2(float x) { float y; asm("ex2.approx.ftz.f32 %0, %1;" : "=f"(y) : "f"(x)); return y; }
__device__ __forceinline__ uint32_t pack_bf16(float lo, float hi) {
    __nv_bfloat162 v = __floats2bfloat162_rn(lo, hi);
    return *reinterpret_cast<uint32_t*>(&v);
}
__device__ __forceinline__ float bf_lo(uint32_t v) { return __uint_as_float(v << 16); }
__device__ __forceinline__ float bf_hi(uint32_t v) { return __uint_as_float(v & 0xffff0000u); }
__device__ __forceinline__ float bf16r(float x) { return bf_lo(pack_bf16(x, 0.f)); }
__device__ __forceinline__ float warp_sum(float v) {
#pragma unroll
    for (int o = 16; o > 0; o >>= 1) v += __shfl_xor_sync(0xffffffffu, v, o);
    return v;
}
__device__ __forceinline__ void sts32(uint32_t addr, uint32_t v) { asm volatile("st.shared.b32 [%0], %1;" ::"r"(addr), "r"(v) : "memory"); }
__device__ __forceinline__ void sts32f(uint32_t addr, float v) { asm volatile("st.shared.f32 [%0], %1;" ::"r"(addr), "f"(v) : "memory"); }
__device__ __forceinline__ uint32_t lds32(uint32_t addr) { uint32_t v; asm volatile("ld.volatile.shared.b32 %0, [%1];" : "=r"(v) : "r"(addr) : "memory"); return v; }
__device__ __forceinline__ uint2 lds64(uint32_t addr) { uint2 v; asm volatile("ld.shared.v2.b32 {%0,%1}, [%2];" : "=r"(v.x), "=r"(v.y) : "r"(addr) : "memory"); return v; }
__device__ __forceinline__ uint4 lds128(uint32_t addr) { uint4 v; asm volatile("ld.shared.v4.b32 {%0,%1,%2,%3}, [%4];" : "=r"(v.x), "=r"(v.y), "=r"(v.z), "=r"(v.w) : "r"(addr) : "memory"); return v; }
__device__ __forceinline__ void sts128(uint32_t addr, uint4 v) { asm volatile("st.shared.v4.b32 [%0], {%1,%2,%3,%4};" ::"r"(addr), "r"(v.x), "r"(v.y), "r"(v.z), "r"(v.w) : "memory"); }
__device__ __forceinline__ uint32_t pin32(uint32_t v) { asm volatile("mov.b32 %0, %0;" : "+r"(v)); return v; }
__device__ __forceinline__ void sync_attn() { asm volatile("bar.sync 1, 256;" ::: "memory"); }
__device__ __forceinline__ void sync_comp() { asm volatile("bar.sync 2, 288;" ::: "memory"); }

__device__ __noinline__ float centred_variance(uint32_t x0, uint32_t x1, uint32_t x2, uint32_t x3, uint32_t x4, uint32_t x5, uint32_t x6,
                                               uint32_t x7, uint32_t x8, float mean) {
    const uint32_t xv[9] = {x0, x1, x2, x3, x4, x5, x6, x7, x8};
    float c = 0.f;
#pragma unroll
    for (int i = 0; i < 9; i++) { const float a = bf_lo(xv[i]) - mean, b = bf_hi(xv[i]) - mean; c = fmaf(a, a, fmaf(b, b, c)); }
    return warp_sum(c) * (1.0f / 576.0f);
}
__device__ __forceinline__ void layernorm_row(const uint32_t (&xv)[9], uint32_t dst_addr) {
    float s0 = 0.f, s1 = 0.f, q0 = 0.f, q1 = 0.f;
#pragma unroll
    for (int i = 0; i < 9; i++) {
        const float a = bf_lo(xv[i]), b = bf_hi(xv[i]);
        s0 += a; s1 += b; q0 = fmaf(a, a, q0); q1 = fmaf(b, b, q1);
    }
    float s = s0 + s1, q = q0 + q1;
#pragma unroll
    for (int o = 16; o > 0; o >>= 1) { s += __shfl_xor_sync(0xffffffffu, s, o); q += __shfl_xor_sync(0xffffffffu, q, o); }
    const float mean = s * (1.0f / 576.0f);
    float var = fmaf(-mean, mean, q * (1.0f / 576.0f));
    if (!(mean * mean <= 32.0f * var)) var = centred_variance(xv[0], xv[1], xv[2], xv[3], xv[4], xv[5], xv[6], xv[7], xv[8], mean);
    float den, rcp;
    asm("sqrt.approx.ftz.f32 %0, %1;" : "=f"(den) : "f"(bf16r(bf16r(var) + 1e-5f)));
    asm("rcp.approx.ftz.f32 %0, %1;" : "=f"(rcp) : "f"(bf16r(den)));
    const __nv_bfloat162 mb2 = __float2bfloat162_rn(mean);
#pragma unroll
    for (int i = 0; i < 9; i++) {
        __nv_bfloat162 d2 = __hsub2(*reinterpret_cast<const __nv_bfloat162*>(&xv[i]), mb2);
        const uint32_t du = *reinterpret_cast<uint32_t*>(&d2);
        sts32(dst_addr + 128 * i, pack_bf16(bf_lo(du) * rcp, bf_hi(du) * rcp));
    }
}

template <int KSTEPS, int PITCH>
__device__ __forceinline__ void load_wfrags(uint32_t (&wf)[KSTEPS * 2], uint32_t lane_addr) {
#pragma unroll
    for (int i = 0; i < KSTEPS / 2; i++) {
        uint32_t r[4];
        ldsm_x4_t(r, lane_addr + i * 32 * PITCH);
        wf[4 * i] = r[0]; wf[4 * i + 1] = r[1]; wf[4 * i + 2] = r[2]; wf[4 * i + 3] = r[3];
    }
}
template <int NP, int DEPTH, int NCH>
__device__ __forceinline__ void gemm_tile(float& o0, float& o1, const uint32_t (&wf)[NP * 4], uint32_t a_lane, int npairs) {
    float c[2 * NCH][4];
#pragma unroll
    for (int i = 0; i < 2 * NCH; i++) { c[i][0] = c[i][1] = c[i][2] = c[i][3] = 0.f; }
    uint32_t r[DEPTH][4];
#pragma unroll
    for (int i = 0; i < DEPTH; i++) ldsm_x4(r[i], a_lane + i * 64);
#pragma unroll
    for (int i = 0; i < NP; i++) {
        if (i < NP - 1 || npairs == NP) {
            mma16816(c[(i % NCH) * 2], r[i % DEPTH], wf[4 * i], wf[4 * i + 1]);
            mma16816(c[(i % NCH) * 2 + 1], r[i % DEPTH], wf[4 * i + 2], wf[4 * i + 3]);
        }
        if (i + DEPTH < NP) ldsm_x4(r[i % DEPTH], a_lane + (i + DEPTH) * 64);
    }
    o0 = 0.f; o1 = 0.f;
#pragma unroll
    for (int i = 0; i < NCH; i++) { o0 += c[2 * i][0] + c[2 * i + 1][2]; o1 += c[2 * i][1] + c[2 * i + 1][3]; }
}
template <int ACT_P>
__device__ __forceinline__ uint32_t act_lane_off(int lane) { return (lane & 7) * ACT_P + ((((lane >> 3) & 1) << 1) | (lane >> 4)) * 16; }

__global__ void __launch_bounds__(NTHREADS, 1)
fused_decode_kernel(const __grid_constant__ Params p) {
    extern __shared__ __align__(1024) uint8_t smem_raw[];
    const uint32_t sb = smem_u32(smem_raw);
    const int tid = threadIdx.x, lane = tid & 31;
    const int warp = __shfl_sync(0xffffffffu, tid >> 5, 0);
    const int cta = blockIdx.x, g = cta >> 3, j = cta & 7;
    const uint32_t bars = sb + SM_BAR;

    if (warp == 9) {
        uint32_t leader;
        asm volatile("{\n.reg .pred p;\nelect.sync _|p, 0xffffffff;\nselp.u32 %0, 1, 0, p;\n}" : "=r"(leader));
        const uint32_t sb = pin32(smem_u32(smem_raw)), bars = sb + SM_BAR;
        const long long t_start = clock64();
        uint64_t stream_pol;
        asm volatile("createpolicy.fractional.L2::evict_first.b64 %0, 1.0;" : "=l"(stream_pol));
        int row = (j * 16 + g) * SK + (SK - WIN);
        if (leader) {
#pragma unroll
            for (int b = 0; b < W_START; b++) mbar_init(bars + b * 8, 1);
            asm volatile("fence.proxy.async.shared::cta;" ::: "memory");
#pragma unroll
            for (int b = 0; b < W_START; b++) mbar_expect_tx(bars + b * 8, TILE_BYTES / 2);
        }
        while (clock64() - t_start < K_DELAY) { }
        uint32_t u = 0;
        uint32_t lu = 0, lpar = 0;
        int landed = 0;
        uint32_t es = 4, epar = 0;
#pragma unroll 1
        for (int i = 0; i < 64; i++) {
            if (i == W_START) {
                if (leader) {
#pragma unroll 1
                    for (int b = W_START; b < 26; b++) mbar_init(bars + b * 8, (b >= BAR_EMPTY && b < BAR_W) ? 8 : 1);
                    sts32(sb + SM_WDYN, W_BULK); sts32(sb + SM_PROG, W_START);
                    if (sb & 1023u) __trap();
                    asm volatile("fence.proxy.async.shared::cta;" ::: "memory");
                }
                __syncthreads();
            }
            const int w = i < B_BULK ? W_START : (int)lds32(sb + SM_WDYN);
#pragma unroll 1
            while (landed <= i - w) {
                mbar_wait(bars + (BAR_FULL + lu) * 8, lpar);
                landed++;
                if (++lu == 2 * NSLOT) { lu = 0; lpar ^= 1; }
            }
            if (i >= 8 && (i & 1) == 0) {
                mbar_wait(bars + (BAR_EMPTY + es) * 8, epar);
                if (++es == NSLOT) es = 0;
                if (es == 4) epar ^= 1;
            }
            if (leader) {
                const CUtensorMap* tm = i < 32 ? &p.tmK : &p.tmV;
                const uint32_t bar = bars + (BAR_FULL + u) * 8;
                const uint32_t dst = sb + (u >> 1) * TILE_BYTES + (u & 1) * (TILE_BYTES / 4);
                if (i >= W_START) mbar_expect_tx(bar, TILE_BYTES / 2);
                tma2d_hint(dst, tm, 0, row, bar, stream_pol);
                tma2d_hint(dst + TILE_BYTES / 2, tm, 64, row, bar, stream_pol);
                if (i >= W_START) {
                    asm volatile("red.relaxed.gpu.global.add.u32 [%0], %1;" ::"l"(p.epoch + 8), "r"(i == W_START ? W_START + 1 : 1) : "memory");
                    sts32(sb + SM_PROG, i + 1);
                }
            }
            row += i == 31 ? TILE_KEYS / 2 - WIN : TILE_KEYS / 2;
            if (++u == 2 * NSLOT) u = 0;
        }
#pragma unroll 1
        for (int k = 0; k < 7; k++) {
            if (k < 2) {
#pragma unroll 1
                while (landed <= 64 + k - W_WO) {
                    mbar_wait(bars + (BAR_FULL + lu) * 8, lpar);
                    landed++;
                    if (++lu == 2 * NSLOT) { lu = 0; lpar ^= 1; }
                }
            } else {
                mbar_wait(bars + (BAR_W + k - W_END) * 8, 0);
            }
            if (k == HOLD_K) mbar_wait(bars + BAR_GO * 8, 0);
            if ((0x2b >> k) & 1) {
                mbar_wait(bars + (BAR_EMPTY + es) * 8, epar);
                if (++es == NSLOT) es = 0;
                if (es == 4) epar ^= 1;
            }
            if (leader) {
                const bool is1 = k >= 2 && k < 5;
                const CUtensorMap* tm = &p.tmWo + (k < 2 ? 0 : (is1 ? 1 : 2));
                const int4 it = p.witem[k];
                mbar_expect_tx(bars + (BAR_W + k) * 8, it.y);
                tma2d(sb + it.x, tm, is1 ? (g * 288 + j * 36) & ~7 : j * 72, g * it.z + it.w, bars + (BAR_W + k) * 8);
            }
        }
        return;
    }

    const int g8 = lane >> 2, t4 = lane & 3;
    unsigned long long* const scratch = p.scratch;
    const bool is_attn = warp < 8;
    const bool is_red = warp < 4 && g < 9;
    const int red_row = 2 * warp + ((lane >> 2) & 1);
    uint32_t hv[9];
    uint32_t res = 0;
    if (is_attn) {
        const uint32_t* xr = reinterpret_cast<const uint32_t*>(p.x + warp * D_MODEL) + lane;
#pragma unroll
        for (int i = 0; i < 9; i++) hv[i] = __ldg(xr + 32 * i);
    }
    if (is_red) res = __ldg(reinterpret_cast<const uint32_t*>(p.x + red_row * D_MODEL + j * 72 + g * 8) + t4);
    if (is_attn) {
        const __nv_bfloat16* src = p.wq + (tid >> 2) * 4096 + g * 256 + j * 32 + (tid & 3) * 8;
        uint32_t dst = sb + WQ_OFF + (tid >> 2) * 80 + (tid & 3) * 16;
#pragma unroll 1
        for (int i = 0; i < 9; i++) {
            asm volatile("cp.async.cg.shared.global [%0], [%1], 16;" ::"r"(dst), "l"(src) : "memory");
            src += 64 * 4096; dst += 64 * 80;
        }
        asm volatile("cp.async.commit_group;" ::: "memory");
    }
    uint32_t tag;
    asm volatile("ld.relaxed.gpu.global.u32 %0, [%1];" : "=r"(tag) : "l"(p.epoch) : "memory");
    const uint32_t q_out = QLL_OFF + (g * 8 + g8) * 128 + j * 16 + warp * 4 + t4;
    const uint32_t o_out = pin32(OLL_OFF + cta * 128 + ((lane >> 3) & 1) * 64 + warp * 8 + ((lane >> 2) & 1) * 4 + (lane & 3));
    const uint32_t part_out = pin32(HLL_OFF + ((warp * 8 + j) * 16 + g) * 64 + lane * 2);
    const int a_col = warp * 8 + 2 * t4 - (j & 1) * 4;
    const bool a_valid = warp < 5 && a_col >= 0 && a_col < 36;
    const uint32_t x_out = pin32(ALL_OFF + (g * 8 + g8) * 144 + j * 18 + (a_col >> 1));
    const uint32_t hb_out = pin32(HB_OFF + (lane >> 3) * 2304 + red_row * 288 + j * 36 + g * 4 + t4);
    const uint32_t x_in = pin32(HB_OFF + (cta % HB_COPIES) * 2304 + warp * 288 + lane);
    const uint32_t red_in = pin32(HLL_OFF + cta * 1024 + (lane >> 3) * 64 + ((warp & 3) * 8 + (lane & 7)) * 2);
    const uint32_t ln_dst = pin32(sb + SM_ACT + warp * ACT_PITCH * 2 + lane * 4);
    const uint32_t gat_dst_a = pin32(sb + SM_GAT + (tid / 36) * (A_PITCH * 2) + (tid % 36) * 16);
    if (warp < 4) st_pkt(scratch + q_out, 0u, 0u);
    tag += 1;
    __syncthreads();

#pragma unroll 1
    for (int ph = 0; ph < 2; ph++) {
        float o0, o1;
        if (is_attn) {
            uint32_t wf[72];
            if (ph == 0) {
                asm volatile("cp.async.wait_group 0;" ::: "memory");
                sync_attn();
            }
            if (warp < 5) {
                if (ph) mbar_wait_n<3>(bars + (BAR_W + 2) * 8);
                load_wfrags<36, 80>(wf, sb + (ph ? W1_OFF : WQ_OFF) + lane * 80 + warp * 16);
                if (ph == 0) {
                    __syncwarp();
                    if (lane < (warp < 3 ? 2 : 1)) { mbar_arrive(bars + (BAR_EMPTY + 4) * 8); mbar_arrive(bars + (BAR_EMPTY + 5) * 8); }
                }
            }
            if (ph) {
                wait_first(scratch + x_in + 256, tag, lane, H_BACKOFF);
                poll_pkts<9, 32>(scratch + x_in, hv, tag);
            }
            layernorm_row(hv, ln_dst);
            sync_attn();
            if (warp < 5) {
                gemm_tile<18, 4, 3>(o0, o1, wf, sb + SM_ACT + act_lane_off<ACT_PITCH * 2>(lane), 18);
                uint32_t f = pack_bf16(o0, o1);
                if (ph) f = pack_bf16(fmaxf(bf_lo(f), 0.f), fmaxf(bf_hi(f), 0.f));
                if (ph ? a_valid : (warp < 4)) st_pkt(scratch + (ph ? x_out : q_out), f, tag);
            }
            if (ph == 0) {
                if (tid < 128) {
                    uint32_t v[1];
                    poll_pkts<1, 1>(scratch + QLL_OFF + cta * 128 + tid, v, tag);
                    sts32(sb + SM_QS + ((tid & 64) + (tid & 3) * 16 + ((tid & 63) >> 2)) * 4, v[0]);
                }
                sync_attn();
                uint32_t qf[16];
#pragma unroll
                for (int s = 0; s < 4; s++) {
                    const uint4 v = lds128(sb + SM_QS + ((g8 & 1) * 64 + t4 * 16) * 4 + s * 16);
                    qf[4 * s] = v.x; qf[4 * s + 1] = v.y; qf[4 * s + 2] = v.z; qf[4 * s + 3] = v.w;
                }

                float m0 = -INFINITY, m1 = -INFINITY;
                {
                    const int krow = warp * 16 + (lane & 7) + ((lane >> 3) & 1) * 8;
                    const uint32_t rowoff = krow * 128;
                    const uint32_t chi = lane >> 4;
                    const uint32_t sw = krow & 7;
                    uint32_t slot = 0, par = 0;
                    uint32_t wsc = sb + SM_SC + ((warp >> 1) * 40 + (warp & 1) * 16 + g8) * 4;
#pragma unroll 1
                    for (int n = 0; n < NTILE; n++) {
                        mbar_wait(bars + (BAR_FULL + 2 * slot + (warp >> 2)) * 8, par);
                        const uint32_t base = sb + slot * TILE_BYTES + rowoff;
                        float c0[4] = {0.f, 0.f, 0.f, 0.f}, c1[4] = {0.f, 0.f, 0.f, 0.f};
#pragma unroll
                        for (int s = 0; s < 8; s += 2) {
                            uint32_t a[4], b[4];
                            ldsm_x4(a, base + (s >> 2) * (TILE_BYTES / 2) + ((((s & 3) * 2 + chi) ^ sw) << 4));
                            ldsm_x4(b, base + (s >> 2) * (TILE_BYTES / 2) + ((((s & 3) * 2 + 2 + chi) ^ sw) << 4));
                            mma16816(c0, a, qf[2 * s], qf[2 * s + 1]);
                            mma16816(c1, b, qf[2 * s + 2], qf[2 * s + 3]);
                        }
                        __syncwarp();
                        if (lane == 0) mbar_arrive(bars + (BAR_EMPTY + slot) * 8);
                        const float scale = 0.08838834764831845f;
                        const uint32_t u0 = pack_bf16(c0[0] + c1[0], c0[1] + c1[1]), u1 = pack_bf16(c0[2] + c1[2], c0[3] + c1[3]);
                        const uint32_t s0 = pack_bf16(bf_lo(u0) * scale, bf_hi(u0) * scale), s1 = pack_bf16(bf_lo(u1) * scale, bf_hi(u1) * scale);
                        m0 = fmaxf(m0, fmaxf(bf_lo(s0), bf_lo(s1)));
                        m1 = fmaxf(m1, fmaxf(bf_hi(s0), bf_hi(s1)));
                        if (t4 == 0) { sts32(wsc, s0); sts32(wsc + 32, s1); }
                        wsc += 4 * 40 * 4;
                        if (++slot == NSLOT) { slot = 0; par ^= 1; }
                    }
                }
                {
#pragma unroll
                    for (int o = 16; o > 2; o >>= 1) { m0 = fmaxf(m0, __shfl_xor_sync(0xffffffffu, m0, o)); m1 = fmaxf(m1, __shfl_xor_sync(0xffffffffu, m1, o)); }
                    if (lane == 0) { sts32f(sb + SM_RED + warp * 4, m0); sts32f(sb + SM_RED + 32 + warp * 4, m1); }
                    sync_attn();
                    uint2 sv[4];
#pragma unroll
                    for (int i = 0; i < 4; i++) sv[i] = lds64(sb + SM_SC + ((tid >> 2) * 40 + 2 * t4 + 8 * i) * 4);
                    sync_attn();
#pragma unroll 1
                    for (int h = 0; h < 2; h++) {
                        const uint4 a = lds128(sb + SM_RED + h * 32), b = lds128(sb + SM_RED + h * 32 + 16);
                        const float m = fmaxf(fmaxf(fmaxf(__uint_as_float(a.x), __uint_as_float(a.y)), fmaxf(__uint_as_float(a.z), __uint_as_float(a.w))),
                                              fmaxf(fmaxf(__uint_as_float(b.x), __uint_as_float(b.y)), fmaxf(__uint_as_float(b.z), __uint_as_float(b.w))));
                        const uint32_t sel = h ? 0x3244u : 0x1044u;
                        const float l2e = 1.4426950408889634f, ml = -m * l2e;
                        float e[8], sum = 0.f;
#pragma unroll
                        for (int i = 0; i < 4; i++) {
                            e[2 * i] = ex2(fmaf(__uint_as_float(__byte_perm(sv[i].x, 0u, sel)), l2e, ml));
                            e[2 * i + 1] = ex2(fmaf(__uint_as_float(__byte_perm(sv[i].y, 0u, sel)), l2e, ml));
                            sum += e[2 * i] + e[2 * i + 1];
                        }
                        sum = warp_sum(sum);
                        if (lane == 0) sts32f(sb + SM_RED + 64 + h * 32 + warp * 4, sum);
                        sync_attn();
                        const uint4 c = lds128(sb + SM_RED + 64 + h * 32), d = lds128(sb + SM_RED + 80 + h * 32);
                        const float tot = ((__uint_as_float(c.x) + __uint_as_float(c.y)) + (__uint_as_float(c.z) + __uint_as_float(c.w))) +
                                          ((__uint_as_float(d.x) + __uint_as_float(d.y)) + (__uint_as_float(d.z) + __uint_as_float(d.w)));
                        const float inv = __fdividef(1.0f, tot);
                        sts128(sb + SM_SC + h * P_HEAD_STRIDE + tid * 16, make_uint4(pack_bf16(e[0] * inv, e[1] * inv), pack_bf16(e[2] * inv, e[3] * inv),
                                                                                     pack_bf16(e[4] * inv, e[5] * inv), pack_bf16(e[6] * inv, e[7] * inv)));
                    }
                    sync_attn();
                }
                float c0[4] = {0.f, 0.f, 0.f, 0.f}, c1[4] = {0.f, 0.f, 0.f, 0.f};
                {
                    const int krow = (lane & 7) + (lane >> 4) * 8;
                    const uint32_t chunk = (warp & 3) * 2 + ((lane >> 3) & 1);
                    const uint32_t lane_off = (warp >> 2) * (TILE_BYTES / 2) + krow * 128 + ((chunk ^ (lane & 7)) << 4);
                    uint32_t pb = sb + SM_SC + (g8 & 1) * P_HEAD_STRIDE + t4 * 16;
                    uint32_t slot = NTILE % NSLOT, par = (NTILE / NSLOT) & 1;
#pragma unroll 1
                    for (int n = NTILE; n < 2 * NTILE; n++) {
                        const uint32_t base = sb + slot * TILE_BYTES + lane_off;
#pragma unroll
                        for (int s = 0; s < 8; s += 2) {
                            if ((s & 3) == 0) mbar_wait(bars + (BAR_FULL + 2 * slot + (s >> 2)) * 8, par);
                            uint32_t a[4], b[4];
                            const uint4 pv = lds128(pb + (s >> 1) * 64);
                            ldsm_x4_t(a, base + s * 2048);
                            ldsm_x4_t(b, base + (s + 1) * 2048);
                            mma16816(c0, a, pv.x, pv.y);
                            mma16816(c1, b, pv.z, pv.w);
                        }
                        __syncwarp();
                        if (lane == 0) mbar_arrive(bars + (BAR_EMPTY + slot) * 8);
                        pb += 256;
                        if (++slot == NSLOT) { slot = 0; par ^= 1; }
                        if (n == PREWRITE_TILE) {
                            if (lane < 16) st_pkt(scratch + o_out, 0u, 0u);
                            st_pkt2(scratch + part_out, 0u, 0u, 0u); st_pkt2(scratch + part_out + (YLL_OFF - HLL_OFF), 0u, 0u, 0u);
                            if (a_valid) st_pkt(scratch + x_out, 0u, 0u);
                            if (is_red) st_pkt(scratch + hb_out, 0u, 0u);
                            if (warp == 0) asm volatile("bar.arrive 3, 64;" ::: "memory");
                        }
                    }
                }
                const uint32_t pa = pack_bf16(c0[0] + c1[0], c0[1] + c1[1]);
                const uint32_t pb2 = pack_bf16(c0[2] + c1[2], c0[3] + c1[3]);
                const int src = (lane & 3) * 8;
                const uint32_t a0 = __shfl_sync(0xffffffffu, pa, src), a1 = __shfl_sync(0xffffffffu, pa, src + 4);
                const uint32_t b0 = __shfl_sync(0xffffffffu, pb2, src), b1 = __shfl_sync(0xffffffffu, pb2, src + 4);
                const uint32_t lo = (lane & 4) ? b0 : a0, hi = (lane & 4) ? b1 : a1;
                if (lane < 16) st_pkt(scratch + o_out, __byte_perm(lo, hi, (lane & 8) ? 0x7632 : 0x5410), tag);
            }
        } else if (ph == 0) {
            if (lane == 0) {
                const uint32_t base = (tag - 1) * (NCTA * 64);
                uint32_t own, n = 0;
                do {
                    uint32_t tot;
                    asm volatile("ld.relaxed.gpu.global.u32 %0, [%1];" : "=r"(tot) : "l"(p.epoch + 8) : "memory");
                    own = lds32(sb + SM_PROG);
                    const int lead = (int)(own * NCTA) - (int)(tot - base);
                    int w = W_BULK - (lead * BAL_GAIN + (lead >= 0 ? 64 * 16 : -64 * 16)) / (NCTA * 16);
                    w = w < W_MIN ? W_MIN : (w > W_MAX ? W_MAX : w);
                    asm volatile("st.volatile.shared.b32 [%0], %1;" ::"r"(sb + SM_WDYN), "r"(w) : "memory");
                    __nanosleep(BAL_SLEEP);
                } while (own < 60 && ++n < 100000);
            }
            __syncwarp();
            asm volatile("bar.sync 3, 64;" ::: "memory");
            st_pkt2(scratch + part_out, 0u, 0u, 0u); st_pkt2(scratch + part_out + (YLL_OFF - HLL_OFF), 0u, 0u, 0u);

        }

        {
            uint32_t wf[36];
            mbar_wait_n<2>(bars + (BAR_W + 5 * ph) * 8);
            load_wfrags<18, 144>(wf, sb + (ph ? W2_OFF : WO_OFF) + lane * 144 + warp * 16);
            if (ph || is_attn) {
                uint32_t v[4];
                const unsigned long long* src = scratch + ((ph ? ALL_OFF + g * 1152 : OLL_OFF + g * 1024) + tid * 4);
                if (ph == 0) wait_first(src, tag, lane, O_BACKOFF);
                if (ph) spin_cycles(A_DELAY);
                poll_pairs<2, 2>(src, v, tag);
                sts128(ph ? gat_dst_a : sb + SM_GAT + warp * (A_PITCH * 2) + lane * 16, make_uint4(v[0], v[1], v[2], v[3]));
            }
            sync_comp();
            if (ph == 0 && tid == 0) mbar_arrive(bars + BAR_GO * 8);
            gemm_tile<9, 9, 2>(o0, o1, wf, sb + SM_GAT + act_lane_off<A_PITCH * 2>(lane), ph ? 9 : 8);
            st_pkt2(scratch + (part_out + (ph ? YLL_OFF - HLL_OFF : 0)), __float_as_uint(o0), __float_as_uint(o1), tag);
        }
        if (is_red) {
            uint32_t v[8];
            spin_cycles(ph ? RED_DELAY1 : RED_DELAY0);
            poll_pairs<4, 256>(scratch + (red_in + (ph ? YLL_OFF - HLL_OFF : 0)), v, tag);
            float s0 = (__uint_as_float(v[0]) + __uint_as_float(v[2])) + (__uint_as_float(v[4]) + __uint_as_float(v[6]));
            float s1 = (__uint_as_float(v[1]) + __uint_as_float(v[3])) + (__uint_as_float(v[5]) + __uint_as_float(v[7]));
            s0 += __shfl_xor_sync(0xffffffffu, s0, 8); s1 += __shfl_xor_sync(0xffffffffu, s1, 8);
            s0 += __shfl_xor_sync(0xffffffffu, s0, 16); s1 += __shfl_xor_sync(0xffffffffu, s1, 16);
            const uint32_t t = pack_bf16(s0, s1);
            res = pack_bf16(bf_lo(res) + bf_lo(t), bf_hi(res) + bf_hi(t));
            if (ph == 0) {
                st_pkt(scratch + hb_out, res, tag);
            } else {
                if (lane < 8) *reinterpret_cast<uint32_t*>(p.out + red_row * D_MODEL + j * 72 + g * 8 + 2 * t4) = res;
                if (cta == 0 && tid == 0) asm volatile("st.relaxed.gpu.global.u32 [%0], %1;" ::"l"(p.epoch), "r"(tag) : "memory");
            }
        }
    }
}

typedef CUresult (*EncodeTiledFn)(CUtensorMap*, CUtensorMapDataType, cuuint32_t, void*, const cuuint64_t*, const cuuint64_t*,
                                  const cuuint32_t*, const cuuint32_t*, CUtensorMapInterleave, CUtensorMapSwizzle,
                                  CUtensorMapL2promotion, CUtensorMapFloatOOBfill);

void make_map(EncodeTiledFn enc, CUtensorMap* tm, const void* ptr, uint64_t cols, uint64_t rows, uint32_t box_cols, uint32_t box_rows,
              CUtensorMapSwizzle sw) {
    cuuint64_t gd[2] = {cols, rows};
    cuuint64_t gs[1] = {cols * 2};
    cuuint32_t bd[2] = {box_cols, box_rows};
    cuuint32_t es[2] = {1, 1};
    enc(tm, CU_TENSOR_MAP_DATA_TYPE_BFLOAT16, 2, const_cast<void*>(ptr), gd, gs, bd, es, CU_TENSOR_MAP_INTERLEAVE_NONE, sw,
        sw == CU_TENSOR_MAP_SWIZZLE_NONE ? CU_TENSOR_MAP_L2_PROMOTION_L2_128B : CU_TENSOR_MAP_L2_PROMOTION_L2_256B, CU_TENSOR_MAP_FLOAT_OOB_FILL_NONE);
}

}


extern "C" void kernel_launch(void* const* d_in, const int* in_sizes, int n_in, void* d_out, int out_size) {
    (void)in_sizes; (void)n_in; (void)out_size;
    static EncodeTiledFn enc = nullptr;
    static unsigned long long* scratch = nullptr;
    static unsigned int* epoch = nullptr;
    if (!enc) {
        cudaDriverEntryPointQueryResult qr;
        void* fn = nullptr;
        cudaGetDriverEntryPoint("cuTensorMapEncodeTiled", &fn, cudaEnableDefault, &qr);
        enc = (EncodeTiledFn)fn;
        cudaFuncSetAttribute(fused_decode_kernel, cudaFuncAttributeMaxDynamicSharedMemorySize, SMEM_BYTES);
        cudaGetSymbolAddress((void**)&scratch, g_scratch);
        cudaGetSymbolAddress((void**)&epoch, g_epoch);
    }
    Params p;
    make_map(enc, &p.tmK, d_in[1], 128, 8ull * 16 * SK, 64, TILE_KEYS / 2, CU_TENSOR_MAP_SWIZZLE_128B);
    make_map(enc, &p.tmV, d_in[2], 128, 8ull * 16 * SK, 64, TILE_KEYS / 2, CU_TENSOR_MAP_SWIZZLE_128B);
    make_map(enc, &p.tmWo, d_in[4], 576, 4096, 72, 128, CU_TENSOR_MAP_SWIZZLE_NONE);
    make_map(enc, &p.tmW1, d_in[6], 4608, 576, 40, 192, CU_TENSOR_MAP_SWIZZLE_NONE);
    make_map(enc, &p.tmW2, d_in[7], 576, 4608, 72, 144, CU_TENSOR_MAP_SWIZZLE_NONE);
    for (int k = 0; k < 7; k++) {
        if (k < 2) p.witem[k] = make_int4(WO_OFF + k * 128 * 144, 128 * 144, 256, k * 128);
        else if (k < 5) p.witem[k] = make_int4(W1_OFF + (k - 2) * 192 * 80, 192 * 80, 0, (k - 2) * 192);
        else p.witem[k] = make_int4(W2_OFF + (k - 5) * 144 * 144, 144 * 144, 288, (k - 5) * 144);
    }
    p.x = (const __nv_bfloat16*)d_in[0];
    p.wq = (const __nv_bfloat16*)d_in[3];
    p.out = (__nv_bfloat16*)d_out;
    p.scratch = scratch;
    p.epoch = epoch;
    fused_decode_kernel<<<NCTA, NTHREADS, SMEM_BYTES, cudaStreamPerThread>>>(p);
}
```

```cpp
#include <cuda_runtime.h>
#include <cuda_bf16.h>
#include <cuda.h>
#include <stdint.h>

namespace {

constexpr int D_MODEL = 576;
constexpr int NCTA = 128;
constexpr int NTHREADS = 320;
constexpr int SK = 8192;
constexpr int WIN = 2048;
constexpr int TILE_KEYS = 128;
constexpr int TILE_BYTES = TILE_KEYS * 256;
constexpr int NSLOT = 6;
constexpr int NTILE = WIN / TILE_KEYS;

constexpr int W_START = 4;
constexpr int B_BULK = 8;
constexpr int W_BULK = 4, W_MIN = 3, W_MAX = 8;
constexpr int BAL_GAIN = 16;
constexpr int BAL_SLEEP = 200;
constexpr int W_WO = 4;
constexpr int W_END = 2;
constexpr int HOLD_K = 5;
constexpr int K_DELAY = 2800;
constexpr int PREWRITE_TILE = 30;
constexpr int HB_COPIES = 4;
constexpr int O_BACKOFF = 100, H_BACKOFF = 50;
constexpr int RED_DELAY0 = 800, RED_DELAY1 = 200;

constexpr int SM_SC = NSLOT * TILE_BYTES;
constexpr int SM_ACT = SM_SC + 13312;
constexpr int ACT_PITCH = 584;
constexpr int SM_GAT = SM_ACT + 8 * ACT_PITCH * 2;
constexpr int A_PITCH = 296;
constexpr int SM_QS = SM_GAT + 8 * A_PITCH * 2;
constexpr int SM_RED = SM_QS + 512;
constexpr int SM_WDYN = SM_RED + 192, SM_PROG = SM_RED + 196;
constexpr int SM_BAR = SM_RED + 256;
constexpr int SM_TOTAL = SM_BAR + 256;
constexpr int SMEM_BYTES = SM_TOTAL;

constexpr int WQ_OFF = 4 * TILE_BYTES;
constexpr int WO_OFF = 2 * TILE_BYTES;
constexpr int WO_BYTES = 256 * 144;
constexpr int W1_OFF = WO_OFF + WO_BYTES;
constexpr int W1_BYTES = 576 * 80;
constexpr int W2_OFF = W1_OFF + W1_BYTES;
constexpr int W2_BYTES = 288 * 144;
constexpr int P_HEAD_STRIDE = 4096 + 64;
static_assert(W2_OFF + W2_BYTES <= NSLOT * TILE_BYTES, "weights do not fit");

constexpr int BAR_FULL = 0, BAR_EMPTY = 12, BAR_W = 18, BAR_GO = 25;

constexpr int QLL_OFF = 0;
constexpr int OLL_OFF = QLL_OFF + 16 * 8 * 128;
constexpr int HLL_OFF = OLL_OFF + 16 * 8 * 128;
constexpr int HB_OFF = HLL_OFF + 72 * 16 * 64;
constexpr int ALL_OFF = HB_OFF + HB_COPIES * 2304;
constexpr int YLL_OFF = ALL_OFF + 16 * 8 * 144;
constexpr int SCRATCH_U64 = YLL_OFF + 72 * 16 * 64;

struct __align__(64) Params {
    CUtensorMap tmK, tmV, tmWo, tmW1, tmW2;
    const __nv_bfloat16* x;
    const __nv_bfloat16* wq;
    __nv_bfloat16* out;
    unsigned long long* scratch;
    unsigned int* epoch;
    int4 witem[7];
};

__device__ unsigned long long g_scratch[SCRATCH_U64];
__device__ unsigned int g_epoch[32];

__device__ __forceinline__ uint32_t smem_u32(const void* p) { return (uint32_t)__cvta_generic_to_shared(p); }
__device__ __forceinline__ void mbar_init(uint32_t bar, uint32_t cnt) {
    asm volatile("mbarrier.init.shared::cta.b64 [%0], %1;" ::"r"(bar), "r"(cnt) : "memory");
}
__device__ __forceinline__ void mbar_expect_tx(uint32_t bar, uint32_t bytes) {
    asm volatile("mbarrier.arrive.expect_tx.shared::cta.b64 _, [%0], %1;" ::"r"(bar), "r"(bytes) : "memory");
}
__device__ __forceinline__ void mbar_arrive(uint32_t bar) {
    asm volatile("mbarrier.arrive.shared::cta.b64 _, [%0];" ::"r"(bar) : "memory");
}
__device__ __forceinline__ bool mbar_try(uint32_t bar, uint32_t parity) {
    uint32_t ok;
    asm volatile("{\n.reg .pred p;\nmbarrier.try_wait.parity.shared::cta.b64 p, [%1], %2;\nselp.u32 %0, 1, 0, p;\n}"
                 : "=r"(ok) : "r"(bar), "r"(parity) : "memory");
    return ok != 0;
}
constexpr uint32_t SPIN_LIMIT = 1u << 24;
__device__ __forceinline__ void mbar_wait(uint32_t bar, uint32_t parity) {
    asm volatile("{\n.reg .pred p;\n.reg .u32 n;\nmov.u32 n, 0;\n"
                 "MBW_LOOP:\nmbarrier.try_wait.parity.shared::cta.b64 p, [%0], %1;\n@p bra MBW_DONE;\n"
                 "add.u32 n, n, 1;\nsetp.lt.u32 p, n, 16777216;\n@p bra MBW_LOOP;\ntrap;\nMBW_DONE:\n}"
                 ::"r"(bar), "r"(parity) : "memory");
}
template <int N>
__device__ __forceinline__ void mbar_wait_n(uint32_t bar) {
    uint32_t n = 0;
    while (true) {
        bool ok = true;
#pragma unroll
        for (int i = 0; i < N; i++) ok = mbar_try(bar + i * 8, 0) & ok;
        if (ok) break;
        if (++n > SPIN_LIMIT) __trap();
    }
}
__device__ __forceinline__ void tma2d(uint32_t dst, const CUtensorMap* tm, int c0, int c1, uint32_t bar) {
    asm volatile("cp.async.bulk.tensor.2d.shared::cluster.global.mbarrier::complete_tx::bytes [%0], [%1, {%3, %4}], [%2];"
                 ::"r"(dst), "l"(tm), "r"(bar), "r"(c0), "r"(c1) : "memory");
}
__device__ __forceinline__ void tma2d_hint(uint32_t dst, const CUtensorMap* tm, int c0, int c1, uint32_t bar, uint64_t pol) {
    asm volatile("cp.async.bulk.tensor.2d.shared::cluster.global.mbarrier::complete_tx::bytes.L2::cache_hint [%0], [%1, {%3, %4}], [%2], %5;"
                 ::"r"(dst), "l"(tm), "r"(bar), "r"(c0), "r"(c1), "l"(pol) : "memory");
}
__device__ __forceinline__ void ldsm_x4(uint32_t (&r)[4], uint32_t addr) {
    asm volatile("ldmatrix.sync.aligned.m8n8.x4.shared.b16 {%0,%1,%2,%3}, [%4];"
                 : "=r"(r[0]), "=r"(r[1]), "=r"(r[2]), "=r"(r[3]) : "r"(addr) : "memory");
}
__device__ __forceinline__ void ldsm_x4_t(uint32_t (&r)[4], uint32_t addr) {
    asm volatile("ldmatrix.sync.aligned.m8n8.x4.trans.shared.b16 {%0,%1,%2,%3}, [%4];"
                 : "=r"(r[0]), "=r"(r[1]), "=r"(r[2]), "=r"(r[3]) : "r"(addr) : "memory");
}
__device__ __forceinline__ void ldsm_x2(uint32_t& r0, uint32_t& r1, uint32_t addr) {
    asm volatile("ldmatrix.sync.aligned.m8n8.x2.shared.b16 {%0,%1}, [%2];" : "=r"(r0), "=r"(r1) : "r"(addr) : "memory");
}
__device__ __forceinline__ void mma16816(float (&c)[4], const uint32_t (&a)[4], uint32_t b0, uint32_t b1) {
    asm volatile("mma.sync.aligned.m16n8k16.row.col.f32.bf16.bf16.f32 {%0,%1,%2,%3}, {%4,%5,%6,%7}, {%8,%9}, {%0,%1,%2,%3};"
                 : "+f"(c[0]), "+f"(c[1]), "+f"(c[2]), "+f"(c[3])
                 : "r"(a[0]), "r"(a[1]), "r"(a[2]), "r"(a[3]), "r"(b0), "r"(b1));
}
__device__ __forceinline__ unsigned long long ld_pkt(const unsigned long long* p) {
    unsigned long long v;
    asm volatile("ld.relaxed.gpu.global.u64 %0, [%1];" : "=l"(v) : "l"(p) : "memory");
    return v;
}
__device__ __forceinline__ void st_pkt(unsigned long long* p, uint32_t payload, uint32_t tag) {
    unsigned long long v = ((unsigned long long)tag << 32) | payload;
    asm volatile("st.relaxed.gpu.global.u64 [%0], %1;" ::"l"(p), "l"(v) : "memory");
}
__device__ __forceinline__ void ld_pkt2(const unsigned long long* p, unsigned long long& a, unsigned long long& b) {
    asm volatile("ld.relaxed.gpu.global.v2.u64 {%0,%1}, [%2];" : "=l"(a), "=l"(b) : "l"(p) : "memory");
}
__device__ __forceinline__ void st_pkt2(unsigned long long* p, uint32_t v0, uint32_t v1, uint32_t tag) {
    const unsigned long long a = ((unsigned long long)tag << 32) | v0, b = ((unsigned long long)tag << 32) | v1;
    asm volatile("st.relaxed.gpu.global.v2.u64 [%0], {%1,%2};" ::"l"(p), "l"(a), "l"(b) : "memory");
}
template <int N, int STRIDE>
__device__ __forceinline__ void poll_pkts(const unsigned long long* p, uint32_t (&out)[N], uint32_t tag) {
    uint32_t n = 0;
    while (true) {
        unsigned long long v[N];
#pragma unroll
        for (int i = 0; i < N; i++) v[i] = ld_pkt(p + i * STRIDE);
        uint32_t bad[2] = {0u, 0u};
#pragma unroll
        for (int i = 0; i < N; i++) { bad[i & 1] |= (uint32_t)(v[i] >> 32) ^ tag; out[i] = (uint32_t)v[i]; }
        if (__all_sync(0xffffffffu, (bad[0] | bad[1]) == 0)) break;
        if (++n > SPIN_LIMIT) __trap();
    }
}
template <int N, int STRIDE>
__device__ __forceinline__ void poll_pairs(const unsigned long long* p, uint32_t (&out)[2 * N], uint32_t tag) {
    uint32_t n = 0;
    while (true) {
        unsigned long long v[2 * N];
#pragma unroll
        for (int i = 0; i < N; i++) ld_pkt2(p + i * STRIDE, v[2 * i], v[2 * i + 1]);
        uint32_t bad[4] = {0u, 0u, 0u, 0u};
#pragma unroll
        for (int i = 0; i < 2 * N; i++) { bad[i & 3] |= (uint32_t)(v[i] >> 32) ^ tag; out[i] = (uint32_t)v[i]; }
        if (__all_sync(0xffffffffu, ((bad[0] | bad[1]) | (bad[2] | bad[3])) == 0)) break;
        if (++n > SPIN_LIMIT) __trap();
    }
}
__device__ __forceinline__ void spin_cycles(uint32_t n) { if (n) { const uint32_t t0 = (uint32_t)clock(); while ((uint32_t)clock() - t0 < n) { } } }
__device__ __forceinline__ void wait_first(const unsigned long long* p, uint32_t tag, int lane, uint32_t backoff) {
    if (lane == 0) {
        uint32_t n = 0;
        while ((uint32_t)(ld_pkt(p) >> 32) != tag) {
            if (backoff) __nanosleep(backoff);
            if (++n > SPIN_LIMIT) __trap();
        }
    }
    __syncwarp();
}
__device__ __forceinline__ float ex2(float x) { float y; asm("ex2.approx.ftz.f32 %0, %1;" : "=f"(y) : "f"(x)); return y; }
__device__ __forceinline__ uint32_t pack_bf16(float lo, float hi) {
    __nv_bfloat162 v = __floats2bfloat162_rn(lo, hi);
    return *reinterpret_cast<uint32_t*>(&v);
}
__device__ __forceinline__ float bf_lo(uint32_t v) { return __uint_as_float(v << 16); }
__device__ __forceinline__ float bf_hi(uint32_t v) { return __uint_as_float(v & 0xffff0000u); }
__device__ __forceinline__ float bf16r(float x) { return bf_lo(pack_bf16(x, 0.f)); }
__device__ __forceinline__ float warp_sum(float v) {
#pragma unroll
    for (int o = 16; o > 0; o >>= 1) v += __shfl_xor_sync(0xffffffffu, v, o);
    return v;
}
__device__ __forceinline__ void sts32(uint32_t addr, uint32_t v) { asm volatile("st.shared.b32 [%0], %1;" ::"r"(addr), "r"(v) : "memory"); }
__device__ __forceinline__ void sts32f(uint32_t addr, float v) { asm volatile("st.shared.f32 [%0], %1;" ::"r"(addr), "f"(v) : "memory"); }
__device__ __forceinline__ uint32_t lds32(uint32_t addr) { uint32_t v; asm volatile("ld.volatile.shared.b32 %0, [%1];" : "=r"(v) : "r"(addr) : "memory"); return v; }
__device__ __forceinline__ float lds32f(uint32_t addr) { float v; asm volatile("ld.shared.f32 %0, [%1];" : "=f"(v) : "r"(addr) : "memory"); return v; }
__device__ __forceinline__ uint2 lds64(uint32_t addr) { uint2 v; asm volatile("ld.shared.v2.b32 {%0,%1}, [%2];" : "=r"(v.x), "=r"(v.y) : "r"(addr) : "memory"); return v; }
__device__ __forceinline__ uint4 lds128(uint32_t addr) { uint4 v; asm volatile("ld.shared.v4.b32 {%0,%1,%2,%3}, [%4];" : "=r"(v.x), "=r"(v.y), "=r"(v.z), "=r"(v.w) : "r"(addr) : "memory"); return v; }
__device__ __forceinline__ void sts128(uint32_t addr, uint4 v) { asm volatile("st.shared.v4.b32 [%0], {%1,%2,%3,%4};" ::"r"(addr), "r"(v.x), "r"(v.y), "r"(v.z), "r"(v.w) : "memory"); }
__device__ __forceinline__ uint32_t pin32(uint32_t v) { asm volatile("mov.b32 %0, %0;" : "+r"(v)); return v; }
__device__ __forceinline__ void sync_attn() { asm volatile("bar.sync 1, 256;" ::: "memory"); }
__device__ __forceinline__ void sync_comp() { asm volatile("bar.sync 2, 288;" ::: "memory"); }

__device__ __noinline__ float centred_variance(uint32_t x0, uint32_t x1, uint32_t x2, uint32_t x3, uint32_t x4, uint32_t x5, uint32_t x6,
                                               uint32_t x7, uint32_t x8, float mean) {
    const uint32_t xv[9] = {x0, x1, x2, x3, x4, x5, x6, x7, x8};
    float c = 0.f;
#pragma unroll
    for (int i = 0; i < 9; i++) { const float a = bf_lo(xv[i]) - mean, b = bf_hi(xv[i]) - mean; c = fmaf(a, a, fmaf(b, b, c)); }
    return warp_sum(c) * (1.0f / 576.0f);
}
__device__ __forceinline__ void layernorm_row(const uint32_t (&xv)[9], uint32_t dst_addr) {
    float s0 = 0.f, s1 = 0.f, q0 = 0.f, q1 = 0.f;
#pragma unroll
    for (int i = 0; i < 9; i++) {
        const float a = bf_lo(xv[i]), b = bf_hi(xv[i]);
        s0 += a; s1 += b; q0 = fmaf(a, a, q0); q1 = fmaf(b, b, q1);
    }
    float s = s0 + s1, q = q0 + q1;
#pragma unroll
    for (int o = 16; o > 0; o >>= 1) { s += __shfl_xor_sync(0xffffffffu, s, o); q += __shfl_xor_sync(0xffffffffu, q, o); }
    const float mean = s * (1.0f / 576.0f);
    float var = fmaf(-mean, mean, q * (1.0f / 576.0f));
    if (!(mean * mean <= 32.0f * var)) var = centred_variance(xv[0], xv[1], xv[2], xv[3], xv[4], xv[5], xv[6], xv[7], xv[8], mean);
    float den, rcp;
    asm("sqrt.approx.ftz.f32 %0, %1;" : "=f"(den) : "f"(bf16r(bf16r(var) + 1e-5f)));
    asm("rcp.approx.ftz.f32 %0, %1;" : "=f"(rcp) : "f"(bf16r(den)));
    const __nv_bfloat162 mb2 = __float2bfloat162_rn(mean);
#pragma unroll
    for (int i = 0; i < 9; i++) {
        __nv_bfloat162 d2 = __hsub2(*reinterpret_cast<const __nv_bfloat162*>(&xv[i]), mb2);
        const uint32_t du = *reinterpret_cast<uint32_t*>(&d2);
        sts32(dst_addr + 128 * i, pack_bf16(bf_lo(du) * rcp, bf_hi(du) * rcp));
    }
}

template <int KSTEPS, int PITCH>
__device__ __forceinline__ void load_wfrags(uint32_t (&wf)[KSTEPS * 2], uint32_t lane_addr) {
#pragma unroll
    for (int i = 0; i < KSTEPS / 2; i++) {
        uint32_t r[4];
        ldsm_x4_t(r, lane_addr + i * 32 * PITCH);
        wf[4 * i] = r[0]; wf[4 * i + 1] = r[1]; wf[4 * i + 2] = r[2]; wf[4 * i + 3] = r[3];
    }
}
template <int NP, int DEPTH, int NCH>
__device__ __forceinline__ void gemm_tile(float& o0, float& o1, const uint32_t (&wf)[NP * 4], uint32_t a_lane, int npairs) {
    float c[2 * NCH][4];
#pragma unroll
    for (int i = 0; i < 2 * NCH; i++) { c[i][0] = c[i][1] = c[i][2] = c[i][3] = 0.f; }
    uint32_t r[DEPTH][4];
#pragma unroll
    for (int i = 0; i < DEPTH; i++) ldsm_x4(r[i], a_lane + i * 64);
#pragma unroll
    for (int i = 0; i < NP; i++) {
        if (i < NP - 1 || npairs == NP) {
            mma16816(c[(i % NCH) * 2], r[i % DEPTH], wf[4 * i], wf[4 * i + 1]);
            mma16816(c[(i % NCH) * 2 + 1], r[i % DEPTH], wf[4 * i + 2], wf[4 * i + 3]);
        }
        if (i + DEPTH < NP) ldsm_x4(r[i % DEPTH], a_lane + (i + DEPTH) * 64);
    }
    o0 = 0.f; o1 = 0.f;
#pragma unroll
    for (int i = 0; i < NCH; i++) { o0 += c[2 * i][0] + c[2 * i + 1][2]; o1 += c[2 * i][1] + c[2 * i + 1][3]; }
}
template <int ACT_P>
__device__ __forceinline__ uint32_t act_lane_off(int lane) { return (lane & 7) * ACT_P + ((((lane >> 3) & 1) << 1) | (lane >> 4)) * 16; }

__global__ void __launch_bounds__(NTHREADS, 1)
fused_decode_kernel(const __grid_constant__ Params p) {
    extern __shared__ __align__(1024) uint8_t smem_raw[];
    const uint32_t sb = smem_u32(smem_raw);
    const int tid = threadIdx.x, lane = tid & 31;
    const int warp = __shfl_sync(0xffffffffu, tid >> 5, 0);
    const int cta = blockIdx.x, g = cta >> 3, j = cta & 7;
    const uint32_t bars = sb + SM_BAR;

    if (warp == 9) {
        uint32_t leader;
        asm volatile("{\n.reg .pred p;\nelect.sync _|p, 0xffffffff;\nselp.u32 %0, 1, 0, p;\n}" : "=r"(leader));
        const uint32_t sb = pin32(smem_u32(smem_raw)), bars = sb + SM_BAR;
        const long long t_start = clock64();
        uint64_t stream_pol;
        asm volatile("createpolicy.fractional.L2::evict_first.b64 %0, 1.0;" : "=l"(stream_pol));
        int row = (j * 16 + g) * SK + (SK - WIN);
        if (leader) {
#pragma unroll
            for (int b = 0; b < W_START; b++) mbar_init(bars + b * 8, 1);
            asm volatile("fence.proxy.async.shared::cta;" ::: "memory");
#pragma unroll
            for (int b = 0; b < W_START; b++) mbar_expect_tx(bars + b * 8, TILE_BYTES / 2);
        }
        while (clock64() - t_start < K_DELAY) { }
        uint32_t u = 0;
        uint32_t lu = 0, lpar = 0;
        int landed = 0;
        uint32_t es = 4, epar = 0;
#pragma unroll 1
        for (int i = 0; i < 64; i++) {
            if (i == W_START) {
                if (leader) {
#pragma unroll 1
                    for (int b = W_START; b < 26; b++) mbar_init(bars + b * 8, (b >= BAR_EMPTY && b < BAR_W) ? 8 : 1);
                    sts32(sb + SM_WDYN, W_BULK); sts32(sb + SM_PROG, W_START);
                    if (sb & 1023u) __trap();
                    asm volatile("fence.proxy.async.shared::cta;" ::: "memory");
                }
                __syncthreads();
            }
            const int w = i < B_BULK ? W_START : (int)lds32(sb + SM_WDYN);
#pragma unroll 1
            while (landed <= i - w) {
                mbar_wait(bars + (BAR_FULL + lu) * 8, lpar);
                landed++;
                if (++lu == 2 * NSLOT) { lu = 0; lpar ^= 1; }
            }
            if (i >= 8 && (i & 1) == 0) {
                mbar_wait(bars + (BAR_EMPTY + es) * 8, epar);
                if (++es == NSLOT) es = 0;
                if (es == 4) epar ^= 1;
            }
            if (leader) {
                const CUtensorMap* tm = i < 32 ? &p.tmK : &p.tmV;
                const uint32_t bar = bars + (BAR_FULL + u) * 8;
                const uint32_t dst = sb + (u >> 1) * TILE_BYTES + (u & 1) * (TILE_BYTES / 4);
                if (i >= W_START) mbar_expect_tx(bar, TILE_BYTES / 2);
                tma2d_hint(dst, tm, 0, row, bar, stream_pol);
                tma2d_hint(dst + TILE_BYTES / 2, tm, 64, row, bar, stream_pol);
                if (i >= W_START) {
                    asm volatile("red.relaxed.gpu.global.add.u32 [%0], %1;" ::"l"(p.epoch + 8), "r"(i == W_START ? W_START + 1 : 1) : "memory");
                    sts32(sb + SM_PROG, i + 1);
                }
            }
            row += i == 31 ? TILE_KEYS / 2 - WIN : TILE_KEYS / 2;
            if (++u == 2 * NSLOT) u = 0;
        }
#pragma unroll 1
        for (int k = 0; k < 7; k++) {
            if (k < 2) {
#pragma unroll 1
                while (landed <= 64 + k - W_WO) {
                    mbar_wait(bars + (BAR_FULL + lu) * 8, lpar);
                    landed++;
                    if (++lu == 2 * NSLOT) { lu = 0; lpar ^= 1; }
                }
            } else {
                mbar_wait(bars + (BAR_W + k - W_END) * 8, 0);
            }
            if (k == HOLD_K) mbar_wait(bars + BAR_GO * 8, 0);
            if ((0x2b >> k) & 1) {
                mbar_wait(bars + (BAR_EMPTY + es) * 8, epar);
                if (++es == NSLOT) es = 0;
                if (es == 4) epar ^= 1;
            }
            if (leader) {
                const bool is1 = k >= 2 && k < 5;
                const CUtensorMap* tm = &p.tmWo + (k < 2 ? 0 : (is1 ? 1 : 2));
                const int4 it = p.witem[k];
                mbar_expect_tx(bars + (BAR_W + k) * 8, it.y);
                tma2d(sb + it.x, tm, is1 ? (g * 288 + j * 36) & ~7 : j * 72, g * it.z + it.w, bars + (BAR_W + k) * 8);
            }
        }
        return;
    }

    const int g8 = lane >> 2, t4 = lane & 3;
    unsigned long long* const scratch = p.scratch;
    const bool is_attn = warp < 8;
    const bool is_red = warp < 4 && g < 9;
    const int red_row = 2 * warp + ((lane >> 2) & 1);
    uint32_t hv[9];
    uint32_t res = 0;
    if (is_attn) {
        const uint32_t* xr = reinterpret_cast<const uint32_t*>(p.x + warp * D_MODEL) + lane;
#pragma unroll
        for (int i = 0; i < 9; i++) hv[i] = __ldg(xr + 32 * i);
    }
    if (is_red) res = __ldg(reinterpret_cast<const uint32_t*>(p.x + red_row * D_MODEL + j * 72 + g * 8) + t4);
    if (is_attn) {
        const __nv_bfloat16* src = p.wq + (tid >> 2) * 4096 + g * 256 + j * 32 + (tid & 3) * 8;
        uint32_t dst = sb + WQ_OFF + (tid >> 2) * 80 + (tid & 3) * 16;
#pragma unroll 1
        for (int i = 0; i < 9; i++) {
            asm volatile("cp.async.cg.shared.global [%0], [%1], 16;" ::"r"(dst), "l"(src) : "memory");
            src += 64 * 4096; dst += 64 * 80;
        }
        asm volatile("cp.async.commit_group;" ::: "memory");
    }
    uint32_t tag;
    asm volatile("ld.relaxed.gpu.global.u32 %0, [%1];" : "=r"(tag) : "l"(p.epoch) : "memory");
    const uint32_t q_out = QLL_OFF + (g * 8 + warp) * 128 + j * 16 + (lane >> 1);
    const uint32_t o_out = pin32(OLL_OFF + cta * 128 + ((lane >> 3) & 1) * 64 + warp * 8 + ((lane >> 2) & 1) * 4 + (lane & 3));
    const uint32_t part_out = pin32(HLL_OFF + ((warp * 8 + j) * 16 + g) * 64 + lane * 2);
    const uint32_t x_out = pin32(ALL_OFF + (g * 8 + tid / 36) * 144 + j * 18 + ((tid % 36) >> 1));
    const uint32_t a_src = pin32(sb + SM_SC + ((tid / 36) * 52 + tid % 36 + (j & 1) * 4) * 4);
    const uint32_t hb_out = pin32(HB_OFF + (lane >> 3) * 2304 + red_row * 288 + j * 36 + g * 4 + t4);
    const uint32_t x_in = pin32(HB_OFF + (cta % HB_COPIES) * 2304 + warp * 288 + lane);
    const uint32_t red_in = pin32(HLL_OFF + cta * 1024 + (lane >> 3) * 64 + ((warp & 3) * 8 + (lane & 7)) * 2);
    const uint32_t ln_dst = pin32(sb + SM_ACT + warp * ACT_PITCH * 2 + lane * 4);
    const uint32_t gat_dst_a = pin32(sb + SM_GAT + (tid / 36) * (A_PITCH * 2) + (tid % 36) * 16);
    if (is_attn && (lane & 1) == 0) st_pkt(scratch + q_out, 0u, 0u);
    tag += 1;
    __syncthreads();

#pragma unroll 1
    for (int ph = 0; ph < 2; ph++) {
        if (is_attn) {
            uint32_t wf[5][3][4];
            const int s0 = warp < 4 ? 5 * warp : 4 * warp + 4;
            if (ph == 0) {
                asm volatile("cp.async.wait_group 0;" ::: "memory");
                sync_attn();
            } else {
                mbar_wait_n<3>(bars + (BAR_W + 2) * 8);
            }
            {
                const uint32_t wl = sb + (ph ? W1_OFF : WQ_OFF) + (s0 * 16 + (lane & 7) + ((lane >> 4) << 3)) * 80 + ((lane >> 3) & 1) * 16;
#pragma unroll
                for (int i = 0; i < 5; i++) {
                    if (i < 4 || warp < 4) {
#pragma unroll
                        for (int m = 0; m < 3; m++) ldsm_x4_t(wf[i][m], wl + i * 16 * 80 + m * 32);
                    }
                }
            }
            if (ph == 0) {
                __syncwarp();
                if (lane == 0) { mbar_arrive(bars + (BAR_EMPTY + 4) * 8); mbar_arrive(bars + (BAR_EMPTY + 5) * 8); }
            } else {
                wait_first(scratch + x_in + 256, tag, lane, H_BACKOFF);
                poll_pkts<9, 32>(scratch + x_in, hv, tag);
            }
            layernorm_row(hv, ln_dst);
            sync_attn();
            float c[3][2][4];
#pragma unroll
            for (int m = 0; m < 3; m++) {
#pragma unroll
                for (int h = 0; h < 2; h++) { c[m][h][0] = c[m][h][1] = c[m][h][2] = c[m][h][3] = 0.f; }
            }
            uint32_t bf[5][2];
            const uint32_t bl = sb + SM_ACT + (lane & 7) * (ACT_PITCH * 2) + ((lane >> 3) & 1) * 16 + s0 * 32;
#pragma unroll
            for (int i = 0; i < 5; i++) if (i < 4 || warp < 4) ldsm_x2(bf[i][0], bf[i][1], bl + i * 32);
#pragma unroll
            for (int i = 0; i < 5; i++) {
                if (i < 4 || warp < 4) {
#pragma unroll
                    for (int m = 0; m < 3; m++) mma16816(c[m][i & 1], wf[i][m], bf[i][0], bf[i][1]);
                }
            }
            const uint32_t pw = sb + SM_SC + (warp * 8 * 52 + 2 * t4 * 52 + g8) * 4;
#pragma unroll
            for (int m = 0; m < 3; m++) {
                sts32f(pw + m * 64, c[m][0][0] + c[m][1][0]);
                sts32f(pw + m * 64 + 208, c[m][0][1] + c[m][1][1]);
                sts32f(pw + m * 64 + 32, c[m][0][2] + c[m][1][2]);
                sts32f(pw + m * 64 + 240, c[m][0][3] + c[m][1][3]);
            }
        }
        if (ph || is_attn) {
            if (ph) sync_comp(); else sync_attn();
            const uint32_t pr = ph ? a_src : sb + SM_SC + (warp * 52 + lane) * 4;
            float v[8];
#pragma unroll
            for (int w = 0; w < 8; w++) v[w] = lds32f(pr + w * (8 * 52 * 4));
            float f = ((v[0] + v[1]) + (v[2] + v[3])) + ((v[4] + v[5]) + (v[6] + v[7]));
            if (ph) f = fmaxf(f, 0.f);
            const float fn = __shfl_down_sync(0xffffffffu, f, 1);
            if ((lane & 1) == 0) st_pkt(scratch + (ph ? x_out : q_out), pack_bf16(f, fn), tag);
        }
        if (is_attn) {
            if (ph == 0) {
                if (tid < 128) {
                    uint32_t v[1];
                    poll_pkts<1, 1>(scratch + QLL_OFF + cta * 128 + tid, v, tag);
                    sts32(sb + SM_QS + ((tid & 64) + (tid & 3) * 16 + ((tid & 63) >> 2)) * 4, v[0]);
                }
                sync_attn();
                uint32_t qf[16];
#pragma unroll
                for (int s = 0; s < 4; s++) {
                    const uint4 v = lds128(sb + SM_QS + ((g8 & 1) * 64 + t4 * 16) * 4 + s * 16);
                    qf[4 * s] = v.x; qf[4 * s + 1] = v.y; qf[4 * s + 2] = v.z; qf[4 * s + 3] = v.w;
                }

                float m0 = -INFINITY, m1 = -INFINITY;
                {
                    const int krow = warp * 16 + (lane & 7) + ((lane >> 3) & 1) * 8;
                    const uint32_t rowoff = krow * 128;
                    const uint32_t chi = lane >> 4;
                    const uint32_t sw = krow & 7;
                    uint32_t slot = 0, par = 0;
                    uint32_t wsc = sb + SM_SC + ((warp >> 1) * 40 + (warp & 1) * 16 + g8) * 4;
#pragma unroll 1
                    for (int n = 0; n < NTILE; n++) {
                        mbar_wait(bars + (BAR_FULL + 2 * slot + (warp >> 2)) * 8, par);
                        const uint32_t base = sb + slot * TILE_BYTES + rowoff;
                        float c0[4] = {0.f, 0.f, 0.f, 0.f}, c1[4] = {0.f, 0.f, 0.f, 0.f};
#pragma unroll
                        for (int s = 0; s < 8; s += 2) {
                            uint32_t a[4], b[4];
                            ldsm_x4(a, base + (s >> 2) * (TILE_BYTES / 2) + ((((s & 3) * 2 + chi) ^ sw) << 4));
                            ldsm_x4(b, base + (s >> 2) * (TILE_BYTES / 2) + ((((s & 3) * 2 + 2 + chi) ^ sw) << 4));
                            mma16816(c0, a, qf[2 * s], qf[2 * s + 1]);
                            mma16816(c1, b, qf[2 * s + 2], qf[2 * s + 3]);
                        }
                        __syncwarp();
                        if (lane == 0) mbar_arrive(bars + (BAR_EMPTY + slot) * 8);
                        const float scale = 0.08838834764831845f;
                        const uint32_t u0 = pack_bf16(c0[0] + c1[0], c0[1] + c1[1]), u1 = pack_bf16(c0[2] + c1[2], c0[3] + c1[3]);
                        const uint32_t s0 = pack_bf16(bf_lo(u0) * scale, bf_hi(u0) * scale), s1 = pack_bf16(bf_lo(u1) * scale, bf_hi(u1) * scale);
                        m0 = fmaxf(m0, fmaxf(bf_lo(s0), bf_lo(s1)));
                        m1 = fmaxf(m1, fmaxf(bf_hi(s0), bf_hi(s1)));
                        if (t4 == 0) { sts32(wsc, s0); sts32(wsc + 32, s1); }
                        wsc += 4 * 40 * 4;
                        if (++slot == NSLOT) { slot = 0; par ^= 1; }
                    }
                }
                {
#pragma unroll
                    for (int o = 16; o > 2; o >>= 1) { m0 = fmaxf(m0, __shfl_xor_sync(0xffffffffu, m0, o)); m1 = fmaxf(m1, __shfl_xor_sync(0xffffffffu, m1, o)); }
                    if (lane == 0) { sts32f(sb + SM_RED + warp * 4, m0); sts32f(sb + SM_RED + 32 + warp * 4, m1); }
                    sync_attn();
                    uint2 sv[4];
#pragma unroll
                    for (int i = 0; i < 4; i++) sv[i] = lds64(sb + SM_SC + ((tid >> 2) * 40 + 2 * t4 + 8 * i) * 4);
                    sync_attn();
#pragma unroll 1
                    for (int h = 0; h < 2; h++) {
                        const uint4 a = lds128(sb + SM_RED + h * 32), b = lds128(sb + SM_RED + h * 32 + 16);
                        const float m = fmaxf(fmaxf(fmaxf(__uint_as_float(a.x), __uint_as_float(a.y)), fmaxf(__uint_as_float(a.z), __uint_as_float(a.w))),
                                              fmaxf(fmaxf(__uint_as_float(b.x), __uint_as_float(b.y)), fmaxf(__uint_as_float(b.z), __uint_as_float(b.w))));
                        const uint32_t sel = h ? 0x3244u : 0x1044u;
                        const float l2e = 1.4426950408889634f, ml = -m * l2e;
                        float e[8], sum = 0.f;
#pragma unroll
                        for (int i = 0; i < 4; i++) {
                            e[2 * i] = ex2(fmaf(__uint_as_float(__byte_perm(sv[i].x, 0u, sel)), l2e, ml));
                            e[2 * i + 1] = ex2(fmaf(__uint_as_float(__byte_perm(sv[i].y, 0u, sel)), l2e, ml));
                            sum += e[2 * i] + e[2 * i + 1];
                        }
                        sum = warp_sum(sum);
                        if (lane == 0) sts32f(sb + SM_RED + 64 + h * 32 + warp * 4, sum);
                        sync_attn();
                        const uint4 c = lds128(sb + SM_RED + 64 + h * 32), d = lds128(sb + SM_RED + 80 + h * 32);
                        const float tot = ((__uint_as_float(c.x) + __uint_as_float(c.y)) + (__uint_as_float(c.z) + __uint_as_float(c.w))) +
                                          ((__uint_as_float(d.x) + __uint_as_float(d.y)) + (__uint_as_float(d.z) + __uint_as_float(d.w)));
                        const float inv = __fdividef(1.0f, tot);
                        sts128(sb + SM_SC + h * P_HEAD_STRIDE + tid * 16, make_uint4(pack_bf16(e[0] * inv, e[1] * inv), pack_bf16(e[2] * inv, e[3] * inv),
                                                                                     pack_bf16(e[4] * inv, e[5] * inv), pack_bf16(e[6] * inv, e[7] * inv)));
                    }
                    sync_attn();
                }
                float c0[4] = {0.f, 0.f, 0.f, 0.f}, c1[4] = {0.f, 0.f, 0.f, 0.f};
                {
                    const int krow = (lane & 7) + (lane >> 4) * 8;
                    const uint32_t chunk = (warp & 3) * 2 + ((lane >> 3) & 1);
                    const uint32_t lane_off = (warp >> 2) * (TILE_BYTES / 2) + krow * 128 + ((chunk ^ (lane & 7)) << 4);
                    uint32_t pb = sb + SM_SC + (g8 & 1) * P_HEAD_STRIDE + t4 * 16;
                    uint32_t slot = NTILE % NSLOT, par = (NTILE / NSLOT) & 1;
#pragma unroll 1
                    for (int n = NTILE; n < 2 * NTILE; n++) {
                        const uint32_t base = sb + slot * TILE_BYTES + lane_off;
#pragma unroll
                        for (int s = 0; s < 8; s += 2) {
                            if ((s & 3) == 0) mbar_wait(bars + (BAR_FULL + 2 * slot + (s >> 2)) * 8, par);
                            uint32_t a[4], b[4];
                            const uint4 pv = lds128(pb + (s >> 1) * 64);
                            ldsm_x4_t(a, base + s * 2048);
                            ldsm_x4_t(b, base + (s + 1) * 2048);
                            mma16816(c0, a, pv.x, pv.y);
                            mma16816(c1, b, pv.z, pv.w);
                        }
                        __syncwarp();
                        if (lane == 0) mbar_arrive(bars + (BAR_EMPTY + slot) * 8);
                        pb += 256;
                        if (++slot == NSLOT) { slot = 0; par ^= 1; }
                        if (n == PREWRITE_TILE) {
                            if (lane < 16) st_pkt(scratch + o_out, 0u, 0u);
                            st_pkt2(scratch + part_out, 0u, 0u, 0u); st_pkt2(scratch + part_out + (YLL_OFF - HLL_OFF), 0u, 0u, 0u);
                            if ((lane & 1) == 0) st_pkt(scratch + x_out, 0u, 0u);
                            if (is_red) st_pkt(scratch + hb_out, 0u, 0u);
                            if (warp == 0) asm volatile("bar.arrive 3, 64;" ::: "memory");
                        }
                    }
                }
                const uint32_t pa = pack_bf16(c0[0] + c1[0], c0[1] + c1[1]);
                const uint32_t pb2 = pack_bf16(c0[2] + c1[2], c0[3] + c1[3]);
                const int src = (lane & 3) * 8;
                const uint32_t a0 = __shfl_sync(0xffffffffu, pa, src), a1 = __shfl_sync(0xffffffffu, pa, src + 4);
                const uint32_t b0 = __shfl_sync(0xffffffffu, pb2, src), b1 = __shfl_sync(0xffffffffu, pb2, src + 4);
                const uint32_t lo = (lane & 4) ? b0 : a0, hi = (lane & 4) ? b1 : a1;
                if (lane < 16) st_pkt(scratch + o_out, __byte_perm(lo, hi, (lane & 8) ? 0x7632 : 0x5410), tag);
            }
        } else if (ph == 0) {
            if (lane == 0) {
                const uint32_t base = (tag - 1) * (NCTA * 64);
                uint32_t own, n = 0;
                do {
                    uint32_t tot;
                    asm volatile("ld.relaxed.gpu.global.u32 %0, [%1];" : "=r"(tot) : "l"(p.epoch + 8) : "memory");
                    own = lds32(sb + SM_PROG);
                    const int lead = (int)(own * NCTA) - (int)(tot - base);
                    int w = W_BULK - (lead * BAL_GAIN + (lead >= 0 ? 64 * 16 : -64 * 16)) / (NCTA * 16);
                    w = w < W_MIN ? W_MIN : (w > W_MAX ? W_MAX : w);
                    asm volatile("st.volatile.shared.b32 [%0], %1;" ::"r"(sb + SM_WDYN), "r"(w) : "memory");
                    __nanosleep(BAL_SLEEP);
                } while (own < 60 && ++n < 100000);
            }
            __syncwarp();
            asm volatile("bar.sync 3, 64;" ::: "memory");
            if ((lane & 1) == 0) st_pkt(scratch + x_out, 0u, 0u);
            st_pkt2(scratch + part_out, 0u, 0u, 0u); st_pkt2(scratch + part_out + (YLL_OFF - HLL_OFF), 0u, 0u, 0u);

        }

        {
            float o0, o1;
            uint32_t wf[36];
            mbar_wait_n<2>(bars + (BAR_W + 5 * ph) * 8);
            load_wfrags<18, 144>(wf, sb + (ph ? W2_OFF : WO_OFF) + lane * 144 + warp * 16);
            if (ph || is_attn) {
                uint32_t v[4];
                const unsigned long long* src = scratch + ((ph ? ALL_OFF + g * 1152 : OLL_OFF + g * 1024) + tid * 4);
                if (ph == 0) wait_first(src, tag, lane, O_BACKOFF);
                poll_pairs<2, 2>(src, v, tag);
                sts128(ph ? gat_dst_a : sb + SM_GAT + warp * (A_PITCH * 2) + lane * 16, make_uint4(v[0], v[1], v[2], v[3]));
            }
            sync_comp();
            if (ph == 0 && tid == 0) mbar_arrive(bars + BAR_GO * 8);
            gemm_tile<9, 9, 2>(o0, o1, wf, sb + SM_GAT + act_lane_off<A_PITCH * 2>(lane), ph ? 9 : 8);
            st_pkt2(scratch + (part_out + (ph ? YLL_OFF - HLL_OFF : 0)), __float_as_uint(o0), __float_as_uint(o1), tag);
        }
        if (is_red) {
            uint32_t v[8];
            spin_cycles(ph ? RED_DELAY1 : RED_DELAY0);
            poll_pairs<4, 256>(scratch + (red_in + (ph ? YLL_OFF - HLL_OFF : 0)), v, tag);
            float s0 = (__uint_as_float(v[0]) + __uint_as_float(v[2])) + (__uint_as_float(v[4]) + __uint_as_float(v[6]));
            float s1 = (__uint_as_float(v[1]) + __uint_as_float(v[3])) + (__uint_as_float(v[5]) + __uint_as_float(v[7]));
            s0 += __shfl_xor_sync(0xffffffffu, s0, 8); s1 += __shfl_xor_sync(0xffffffffu, s1, 8);
            s0 += __shfl_xor_sync(0xffffffffu, s0, 16); s1 += __shfl_xor_sync(0xffffffffu, s1, 16);
            const uint32_t t = pack_bf16(s0, s1);
            res = pack_bf16(bf_lo(res) + bf_lo(t), bf_hi(res) + bf_hi(t));
            if (ph == 0) {
                st_pkt(scratch + hb_out, res, tag);
            } else {
                if (lane < 8) *reinterpret_cast<uint32_t*>(p.out + red_row * D_MODEL + j * 72 + g * 8 + 2 * t4) = res;
                if (cta == 0 && tid == 0) asm volatile("st.relaxed.gpu.global.u32 [%0], %1;" ::"l"(p.epoch), "r"(tag) : "memory");
            }
        }
    }
}

typedef CUresult (*EncodeTiledFn)(CUtensorMap*, CUtensorMapDataType, cuuint32_t, void*, const cuuint64_t*, const cuuint64_t*,
                                  const cuuint32_t*, const cuuint32_t*, CUtensorMapInterleave, CUtensorMapSwizzle,
                                  CUtensorMapL2promotion, CUtensorMapFloatOOBfill);

void make_map(EncodeTiledFn enc, CUtensorMap* tm, const void* ptr, uint64_t cols, uint64_t rows, uint32_t box_cols, uint32_t box_rows,
              CUtensorMapSwizzle sw) {
    cuuint64_t gd[2] = {cols, rows};
    cuuint64_t gs[1] = {cols * 2};
    cuuint32_t bd[2] = {box_cols, box_rows};
    cuuint32_t es[2] = {1, 1};
    enc(tm, CU_TENSOR_MAP_DATA_TYPE_BFLOAT16, 2, const_cast<void*>(ptr), gd, gs, bd, es, CU_TENSOR_MAP_INTERLEAVE_NONE, sw,
        sw == CU_TENSOR_MAP_SWIZZLE_NONE ? CU_TENSOR_MAP_L2_PROMOTION_L2_128B : CU_TENSOR_MAP_L2_PROMOTION_L2_256B, CU_TENSOR_MAP_FLOAT_OOB_FILL_NONE);
}

}


extern "C" void kernel_launch(void* const* d_in, const int* in_sizes, int n_in, void* d_out, int out_size) {
    (void)in_sizes; (void)n_in; (void)out_size;
    static EncodeTiledFn enc = nullptr;
    static unsigned long long* scratch = nullptr;
    static unsigned int* epoch = nullptr;
    if (!enc) {
        cudaDriverEntryPointQueryResult qr;
        void* fn = nullptr;
        cudaGetDriverEntryPoint("cuTensorMapEncodeTiled", &fn, cudaEnableDefault, &qr);
        enc = (EncodeTiledFn)fn;
        cudaFuncSetAttribute(fused_decode_kernel, cudaFuncAttributeMaxDynamicSharedMemorySize, SMEM_BYTES);
        cudaGetSymbolAddress((void**)&scratch, g_scratch);
        cudaGetSymbolAddress((void**)&epoch, g_epoch);
    }
    Params p;
    make_map(enc, &p.tmK, d_in[1], 128, 8ull * 16 * SK, 64, TILE_KEYS / 2, CU_TENSOR_MAP_SWIZZLE_128B);
    make_map(enc, &p.tmV, d_in[2], 128, 8ull * 16 * SK, 64, TILE_KEYS / 2, CU_TENSOR_MAP_SWIZZLE_128B);
    make_map(enc, &p.tmWo, d_in[4], 576, 4096, 72, 128, CU_TENSOR_MAP_SWIZZLE_NONE);
    make_map(enc, &p.tmW1, d_in[6], 4608, 576, 40, 192, CU_TENSOR_MAP_SWIZZLE_NONE);
    make_map(enc, &p.tmW2, d_in[7], 576, 4608, 72, 144, CU_TENSOR_MAP_SWIZZLE_NONE);
    for (int k = 0; k < 7; k++) {
        if (k < 2) p.witem[k] = make_int4(WO_OFF + k * 128 * 144, 128 * 144, 256, k * 128);
        else if (k < 5) p.witem[k] = make_int4(W1_OFF + (k - 2) * 192 * 80, 192 * 80, 0, (k - 2) * 192);
        else p.witem[k] = make_int4(W2_OFF + (k - 5) * 144 * 144, 144 * 144, 288, (k - 5) * 144);
    }
    p.x = (const __nv_bfloat16*)d_in[0];
    p.wq = (const __nv_bfloat16*)d_in[3];
    p.out = (__nv_bfloat16*)d_out;
    p.scratch = scratch;
    p.epoch = epoch;
    fused_decode_kernel<<<NCTA, NTHREADS, SMEM_BYTES, cudaStreamPerThread>>>(p);
}
```

```cpp
#include <cuda_runtime.h>
#include <cuda_bf16.h>
#include <cuda.h>
#include <stdint.h>

namespace {

constexpr int D_MODEL = 576;
constexpr int NCTA = 128;
constexpr int NTHREADS = 320;
constexpr int SK = 8192;
constexpr int WIN = 2048;
constexpr int TILE_KEYS = 128;
constexpr int TILE_BYTES = TILE_KEYS * 256;
constexpr int NSLOT = 6;
constexpr int NTILE = WIN / TILE_KEYS;

constexpr int W_START = 4;
constexpr int B_BULK = 8;
constexpr int W_BULK = 4, W_MIN = 3, W_MAX = 8;
constexpr int BAL_GAIN = 16;
constexpr int BAL_SLEEP = 200;
constexpr int W_WO = 4;
constexpr int W_END = 2;
constexpr int HOLD_K = 5;
constexpr int K_DELAY = 2800;
constexpr int PREWRITE_TILE = 26;
constexpr int HB_COPIES = 4;
constexpr int O_BACKOFF = 100, H_BACKOFF = 50;
constexpr int RED_DELAY0 = 800, RED_DELAY1 = 200;

constexpr int SM_SC = NSLOT * TILE_BYTES;
constexpr int SM_ACT = SM_SC + 13312;
constexpr int ACT_PITCH = 584;
constexpr int SM_GAT = SM_ACT + 8 * ACT_PITCH * 2;
constexpr int A_PITCH = 296;
constexpr int SM_QS = SM_GAT + 8 * A_PITCH * 2;
constexpr int SM_RED = SM_QS + 512;
constexpr int SM_WDYN = SM_RED + 192, SM_PROG = SM_RED + 196;
constexpr int SM_BAR = SM_RED + 256;
constexpr int SM_TOTAL = SM_BAR + 256;
constexpr int SMEM_BYTES = SM_TOTAL;

constexpr int WQ_OFF = 4 * TILE_BYTES;
constexpr int WO_OFF = 2 * TILE_BYTES;
constexpr int WO_BYTES = 256 * 144;
constexpr int W1_OFF = WO_OFF + WO_BYTES;
constexpr int W1_BYTES = 576 * 80;
constexpr int W2_OFF = W1_OFF + W1_BYTES;
constexpr int W2_BYTES = 288 * 144;
constexpr int P_HEAD_STRIDE = 4096 + 64;
static_assert(W2_OFF + W2_BYTES <= NSLOT * TILE_BYTES, "weights do not fit");

constexpr int BAR_FULL = 0, BAR_EMPTY = 12, BAR_W = 18, BAR_GO = 25;

constexpr int QLL_OFF = 0;
constexpr int OLL_OFF = QLL_OFF + 16 * 8 * 128;
constexpr int HLL_OFF = OLL_OFF + 16 * 8 * 128;
constexpr int HB_OFF = HLL_OFF + 72 * 16 * 64;
constexpr int ALL_OFF = HB_OFF + HB_COPIES * 2304;
constexpr int YLL_OFF = ALL_OFF + 16 * 8 * 144;
constexpr int SCRATCH_U64 = YLL_OFF + 72 * 16 * 64;

struct __align__(64) Params {
    CUtensorMap tmK, tmV, tmWo, tmW1, tmW2;
    const __nv_bfloat16* x;
    const __nv_bfloat16* wq;
    __nv_bfloat16* out;
    unsigned long long* scratch;
    unsigned int* epoch;
    int4 witem[7];
};

__device__ unsigned long long g_scratch[SCRATCH_U64];
__device__ unsigned int g_epoch[32];

__device__ __forceinline__ uint32_t smem_u32(const void* p) { return (uint32_t)__cvta_generic_to_shared(p); }
__device__ __forceinline__ void mbar_init(uint32_t bar, uint32_t cnt) {
    asm volatile("mbarrier.init.shared::cta.b64 [%0], %1;" ::"r"(bar), "r"(cnt) : "memory");
}
__device__ __forceinline__ void mbar_expect_tx(uint32_t bar, uint32_t bytes) {
    asm volatile("mbarrier.arrive.expect_tx.shared::cta.b64 _, [%0], %1;" ::"r"(bar), "r"(bytes) : "memory");
}
__device__ __forceinline__ void mbar_arrive(uint32_t bar) {
    asm volatile("mbarrier.arrive.shared::cta.b64 _, [%0];" ::"r"(bar) : "memory");
}
__device__ __forceinline__ bool mbar_try(uint32_t bar, uint32_t parity) {
    uint32_t ok;
    asm volatile("{\n.reg .pred p;\nmbarrier.try_wait.parity.shared::cta.b64 p, [%1], %2;\nselp.u32 %0, 1, 0, p;\n}"
                 : "=r"(ok) : "r"(bar), "r"(parity) : "memory");
    return ok != 0;
}
constexpr uint32_t SPIN_LIMIT = 1u << 24;
__device__ __forceinline__ void mbar_wait(uint32_t bar, uint32_t parity) {
    asm volatile("{\n.reg .pred p;\n.reg .u32 n;\nmov.u32 n, 0;\n"
                 "MBW_LOOP:\nmbarrier.try_wait.parity.shared::cta.b64 p, [%0], %1;\n@p bra MBW_DONE;\n"
                 "add.u32 n, n, 1;\nsetp.lt.u32 p, n, 16777216;\n@p bra MBW_LOOP;\ntrap;\nMBW_DONE:\n}"
                 ::"r"(bar), "r"(parity) : "memory");
}
template <int N>
__device__ __forceinline__ void mbar_wait_n(uint32_t bar) {
    uint32_t n = 0;
    while (true) {
        bool ok = true;
#pragma unroll
        for (int i = 0; i < N; i++) ok = mbar_try(bar + i * 8, 0) & ok;
        if (ok) break;
        if (++n > SPIN_LIMIT) __trap();
    }
}
__device__ __forceinline__ void tma2d(uint32_t dst, const CUtensorMap* tm, int c0, int c1, uint32_t bar) {
    asm volatile("cp.async.bulk.tensor.2d.shared::cluster.global.mbarrier::complete_tx::bytes [%0], [%1, {%3, %4}], [%2];"
                 ::"r"(dst), "l"(tm), "r"(bar), "r"(c0), "r"(c1) : "memory");
}
__device__ __forceinline__ void tma2d_hint(uint32_t dst, const CUtensorMap* tm, int c0, int c1, uint32_t bar, uint64_t pol) {
    asm volatile("cp.async.bulk.tensor.2d.shared::cluster.global.mbarrier::complete_tx::bytes.L2::cache_hint [%0], [%1, {%3, %4}], [%2], %5;"
                 ::"r"(dst), "l"(tm), "r"(bar), "r"(c0), "r"(c1), "l"(pol) : "memory");
}
__device__ __forceinline__ void ldsm_x4(uint32_t (&r)[4], uint32_t addr) {
    asm volatile("ldmatrix.sync.aligned.m8n8.x4.shared.b16 {%0,%1,%2,%3}, [%4];"
                 : "=r"(r[0]), "=r"(r[1]), "=r"(r[2]), "=r"(r[3]) : "r"(addr) : "memory");
}
__device__ __forceinline__ void ldsm_x4_t(uint32_t (&r)[4], uint32_t addr) {
    asm volatile("ldmatrix.sync.aligned.m8n8.x4.trans.shared.b16 {%0,%1,%2,%3}, [%4];"
                 : "=r"(r[0]), "=r"(r[1]), "=r"(r[2]), "=r"(r[3]) : "r"(addr) : "memory");
}
__device__ __forceinline__ void ldsm_x2(uint32_t& r0, uint32_t& r1, uint32_t addr) {
    asm volatile("ldmatrix.sync.aligned.m8n8.x2.shared.b16 {%0,%1}, [%2];" : "=r"(r0), "=r"(r1) : "r"(addr) : "memory");
}
__device__ __forceinline__ void mma16816(float (&c)[4], const uint32_t (&a)[4], uint32_t b0, uint32_t b1) {
    asm volatile("mma.sync.aligned.m16n8k16.row.col.f32.bf16.bf16.f32 {%0,%1,%2,%3}, {%4,%5,%6,%7}, {%8,%9}, {%0,%1,%2,%3};"
                 : "+f"(c[0]), "+f"(c[1]), "+f"(c[2]), "+f"(c[3])
                 : "r"(a[0]), "r"(a[1]), "r"(a[2]), "r"(a[3]), "r"(b0), "r"(b1));
}
__device__ __forceinline__ unsigned long long ld_pkt(const unsigned long long* p) {
    unsigned long long v;
    asm volatile("ld.relaxed.gpu.global.u64 %0, [%1];" : "=l"(v) : "l"(p) : "memory");
    return v;
}
__device__ __forceinline__ void st_pkt(unsigned long long* p, uint32_t payload, uint32_t tag) {
    unsigned long long v = ((unsigned long long)tag << 32) | payload;
    asm volatile("st.relaxed.gpu.global.u64 [%0], %1;" ::"l"(p), "l"(v) : "memory");
}
__device__ __forceinline__ void ld_pkt2(const unsigned long long* p, unsigned long long& a, unsigned long long& b) {
    asm volatile("ld.relaxed.gpu.global.v2.u64 {%0,%1}, [%2];" : "=l"(a), "=l"(b) : "l"(p) : "memory");
}
__device__ __forceinline__ void st_pkt2(unsigned long long* p, uint32_t v0, uint32_t v1, uint32_t tag) {
    const unsigned long long a = ((unsigned long long)tag << 32) | v0, b = ((unsigned long long)tag << 32) | v1;
    asm volatile("st.relaxed.gpu.global.v2.u64 [%0], {%1,%2};" ::"l"(p), "l"(a), "l"(b) : "memory");
}
template <int N, int STRIDE>
__device__ __forceinline__ void poll_pkts(const unsigned long long* p, uint32_t (&out)[N], uint32_t tag) {
    uint32_t n = 0;
    while (true) {
        unsigned long long v[N];
#pragma unroll
        for (int i = 0; i < N; i++) v[i] = ld_pkt(p + i * STRIDE);
        uint32_t bad[2] = {0u, 0u};
#pragma unroll
        for (int i = 0; i < N; i++) { bad[i & 1] |= (uint32_t)(v[i] >> 32) ^ tag; out[i] = (uint32_t)v[i]; }
        if (__all_sync(0xffffffffu, (bad[0] | bad[1]) == 0)) break;
        if (++n > SPIN_LIMIT) __trap();
    }
}
template <int N, int STRIDE>
__device__ __forceinline__ void poll_pairs(const unsigned long long* p, uint32_t (&out)[2 * N], uint32_t tag, uint32_t backoff = 0) {
    uint32_t n = 0;
    while (true) {
        unsigned long long v[2 * N];
#pragma unroll
        for (int i = 0; i < N; i++) ld_pkt2(p + i * STRIDE, v[2 * i], v[2 * i + 1]);
        uint32_t bad[4] = {0u, 0u, 0u, 0u};
#pragma unroll
        for (int i = 0; i < 2 * N; i++) { bad[i & 3] |= (uint32_t)(v[i] >> 32) ^ tag; out[i] = (uint32_t)v[i]; }
        if (__all_sync(0xffffffffu, ((bad[0] | bad[1]) | (bad[2] | bad[3])) == 0)) break;
        if (backoff) __nanosleep(backoff);
        if (++n > SPIN_LIMIT) __trap();
    }
}
__device__ __forceinline__ void spin_cycles(uint32_t n) { if (n) { const uint32_t t0 = (uint32_t)clock(); while ((uint32_t)clock() - t0 < n) { } } }
__device__ __forceinline__ void wait_first(const unsigned long long* p, uint32_t tag, int lane, uint32_t backoff) {
    if (lane == 0) {
        uint32_t n = 0;
        while ((uint32_t)(ld_pkt(p) >> 32) != tag) {
            if (backoff) __nanosleep(backoff);
            if (++n > SPIN_LIMIT) __trap();
        }
    }
    __syncwarp();
}
__device__ __forceinline__ float ex2(float x) { float y; asm("ex2.approx.ftz.f32 %0, %1;" : "=f"(y) : "f"(x)); return y; }
__device__ __forceinline__ uint32_t pack_bf16(float lo, float hi) {
    __nv_bfloat162 v = __floats2bfloat162_rn(lo, hi);
    return *reinterpret_cast<uint32_t*>(&v);
}
__device__ __forceinline__ float bf_lo(uint32_t v) { return __uint_as_float(v << 16); }
__device__ __forceinline__ float bf_hi(uint32_t v) { return __uint_as_float(v & 0xffff0000u); }
__device__ __forceinline__ float bf16r(float x) { return bf_lo(pack_bf16(x, 0.f)); }
__device__ __forceinline__ float warp_sum(float v) {
#pragma unroll
    for (int o = 16; o > 0; o >>= 1) v += __shfl_xor_sync(0xffffffffu, v, o);
    return v;
}
__device__ __forceinline__ void sts32(uint32_t addr, uint32_t v) { asm volatile("st.shared.b32 [%0], %1;" ::"r"(addr), "r"(v) : "memory"); }
__device__ __forceinline__ void sts32f(uint32_t addr, float v) { asm volatile("st.shared.f32 [%0], %1;" ::"r"(addr), "f"(v) : "memory"); }
__device__ __forceinline__ uint32_t lds32(uint32_t addr) { uint32_t v; asm volatile("ld.volatile.shared.b32 %0, [%1];" : "=r"(v) : "r"(addr) : "memory"); return v; }
__device__ __forceinline__ float lds32f(uint32_t addr) { float v; asm volatile("ld.shared.f32 %0, [%1];" : "=f"(v) : "r"(addr) : "memory"); return v; }
__device__ __forceinline__ uint2 lds64(uint32_t addr) { uint2 v; asm volatile("ld.shared.v2.b32 {%0,%1}, [%2];" : "=r"(v.x), "=r"(v.y) : "r"(addr) : "memory"); return v; }
__device__ __forceinline__ uint4 lds128(uint32_t addr) { uint4 v; asm volatile("ld.shared.v4.b32 {%0,%1,%2,%3}, [%4];" : "=r"(v.x), "=r"(v.y), "=r"(v.z), "=r"(v.w) : "r"(addr) : "memory"); return v; }
__device__ __forceinline__ void sts128(uint32_t addr, uint4 v) { asm volatile("st.shared.v4.b32 [%0], {%1,%2,%3,%4};" ::"r"(addr), "r"(v.x), "r"(v.y), "r"(v.z), "r"(v.w) : "memory"); }
__device__ __forceinline__ uint32_t pin32(uint32_t v) { asm volatile("mov.b32 %0, %0;" : "+r"(v)); return v; }
__device__ __forceinline__ void sync_attn() { asm volatile("bar.sync 1, 256;" ::: "memory"); }
__device__ __forceinline__ void sync_comp() { asm volatile("bar.sync 2, 288;" ::: "memory"); }

__device__ __noinline__ float centred_variance(uint32_t x0, uint32_t x1, uint32_t x2, uint32_t x3, uint32_t x4, uint32_t x5, uint32_t x6,
                                               uint32_t x7, uint32_t x8, float mean) {
    const uint32_t xv[9] = {x0, x1, x2, x3, x4, x5, x6, x7, x8};
    float c = 0.f;
#pragma unroll
    for (int i = 0; i < 9; i++) { const float a = bf_lo(xv[i]) - mean, b = bf_hi(xv[i]) - mean; c = fmaf(a, a, fmaf(b, b, c)); }
    return warp_sum(c) * (1.0f / 576.0f);
}
__device__ __forceinline__ void layernorm_row(const uint32_t (&xv)[9], uint32_t dst_addr) {
    float s0 = 0.f, s1 = 0.f, q0 = 0.f, q1 = 0.f;
#pragma unroll
    for (int i = 0; i < 9; i++) {
        const float a = bf_lo(xv[i]), b = bf_hi(xv[i]);
        s0 += a; s1 += b; q0 = fmaf(a, a, q0); q1 = fmaf(b, b, q1);
    }
    float s = s0 + s1, q = q0 + q1;
#pragma unroll
    for (int o = 16; o > 0; o >>= 1) { s += __shfl_xor_sync(0xffffffffu, s, o); q += __shfl_xor_sync(0xffffffffu, q, o); }
    const float mean = s * (1.0f / 576.0f);
    float var = fmaf(-mean, mean, q * (1.0f / 576.0f));
    if (!(mean * mean <= 32.0f * var)) var = centred_variance(xv[0], xv[1], xv[2], xv[3], xv[4], xv[5], xv[6], xv[7], xv[8], mean);
    float den, rcp;
    asm("sqrt.approx.ftz.f32 %0, %1;" : "=f"(den) : "f"(bf16r(bf16r(var) + 1e-5f)));
    asm("rcp.approx.ftz.f32 %0, %1;" : "=f"(rcp) : "f"(bf16r(den)));
    const __nv_bfloat162 mb2 = __float2bfloat162_rn(mean);
#pragma unroll
    for (int i = 0; i < 9; i++) {
        __nv_bfloat162 d2 = __hsub2(*reinterpret_cast<const __nv_bfloat162*>(&xv[i]), mb2);
        const uint32_t du = *reinterpret_cast<uint32_t*>(&d2);
        sts32(dst_addr + 128 * i, pack_bf16(bf_lo(du) * rcp, bf_hi(du) * rcp));
    }
}

template <int KSTEPS, int PITCH>
__device__ __forceinline__ void load_wfrags(uint32_t (&wf)[KSTEPS * 2], uint32_t lane_addr) {
#pragma unroll
    for (int i = 0; i < KSTEPS / 2; i++) {
        uint32_t r[4];
        ldsm_x4_t(r, lane_addr + i * 32 * PITCH);
        wf[4 * i] = r[0]; wf[4 * i + 1] = r[1]; wf[4 * i + 2] = r[2]; wf[4 * i + 3] = r[3];
    }
}
template <int NP, int DEPTH, int NCH>
__device__ __forceinline__ void gemm_tile(float& o0, float& o1, const uint32_t (&wf)[NP * 4], uint32_t a_lane, int npairs) {
    float c[2 * NCH][4];
#pragma unroll
    for (int i = 0; i < 2 * NCH; i++) { c[i][0] = c[i][1] = c[i][2] = c[i][3] = 0.f; }
    uint32_t r[DEPTH][4];
#pragma unroll
    for (int i = 0; i < DEPTH; i++) ldsm_x4(r[i], a_lane + i * 64);
#pragma unroll
    for (int i = 0; i < NP; i++) {
        if (i < NP - 1 || npairs == NP) {
            mma16816(c[(i % NCH) * 2], r[i % DEPTH], wf[4 * i], wf[4 * i + 1]);
            mma16816(c[(i % NCH) * 2 + 1], r[i % DEPTH], wf[4 * i + 2], wf[4 * i + 3]);
        }
        if (i + DEPTH < NP) ldsm_x4(r[i % DEPTH], a_lane + (i + DEPTH) * 64);
    }
    o0 = 0.f; o1 = 0.f;
#pragma unroll
    for (int i = 0; i < NCH; i++) { o0 += c[2 * i][0] + c[2 * i + 1][2]; o1 += c[2 * i][1] + c[2 * i + 1][3]; }
}
template <int ACT_P>
__device__ __forceinline__ uint32_t act_lane_off(int lane) { return (lane & 7) * ACT_P + ((((lane >> 3) & 1) << 1) | (lane >> 4)) * 16; }

__global__ void __launch_bounds__(NTHREADS, 1)
fused_decode_kernel(const __grid_constant__ Params p) {
    extern __shared__ __align__(1024) uint8_t smem_raw[];
    const uint32_t sb = smem_u32(smem_raw);
    const int tid = threadIdx.x, lane = tid & 31;
    const int warp = __shfl_sync(0xffffffffu, tid >> 5, 0);
    const int cta = blockIdx.x, g = cta >> 3, j = cta & 7;
    const uint32_t bars = sb + SM_BAR;

    if (warp == 9) {
        uint32_t leader;
        asm volatile("{\n.reg .pred p;\nelect.sync _|p, 0xffffffff;\nselp.u32 %0, 1, 0, p;\n}" : "=r"(leader));
        const uint32_t sb = pin32(smem_u32(smem_raw)), bars = sb + SM_BAR;
        const long long t_start = clock64();
        uint64_t stream_pol;
        asm volatile("createpolicy.fractional.L2::evict_first.b64 %0, 1.0;" : "=l"(stream_pol));
        int row = (j * 16 + g) * SK + (SK - WIN);
        if (leader) {
#pragma unroll
            for (int b = 0; b < W_START; b++) mbar_init(bars + b * 8, 1);
            asm volatile("fence.proxy.async.shared::cta;" ::: "memory");
#pragma unroll
            for (int b = 0; b < W_START; b++) mbar_expect_tx(bars + b * 8, TILE_BYTES / 2);
        }
        while (clock64() - t_start < K_DELAY) { }
        uint32_t u = 0;
        uint32_t lu = 0, lpar = 0;
        int landed = 0;
        uint32_t es = 4, epar = 0;
#pragma unroll 1
        for (int i = 0; i < 64; i++) {
            if (i == W_START) {
                if (leader) {
#pragma unroll 1
                    for (int b = W_START; b < 26; b++) mbar_init(bars + b * 8, (b >= BAR_EMPTY && b < BAR_W) ? 8 : 1);
                    sts32(sb + SM_WDYN, W_BULK); sts32(sb + SM_PROG, W_START);
                    if (sb & 1023u) __trap();
                    asm volatile("fence.proxy.async.shared::cta;" ::: "memory");
                }
                __syncthreads();
            }
            const int w = i < B_BULK ? W_START : (int)lds32(sb + SM_WDYN);
#pragma unroll 1
            while (landed <= i - w) {
                mbar_wait(bars + (BAR_FULL + lu) * 8, lpar);
                landed++;
                if (++lu == 2 * NSLOT) { lu = 0; lpar ^= 1; }
            }
            if (i >= 8 && (i & 1) == 0) {
                mbar_wait(bars + (BAR_EMPTY + es) * 8, epar);
                if (++es == NSLOT) es = 0;
                if (es == 4) epar ^= 1;
            }
            if (leader) {
                const CUtensorMap* tm = i < 32 ? &p.tmK : &p.tmV;
                const uint32_t bar = bars + (BAR_FULL + u) * 8;
                const uint32_t dst = sb + (u >> 1) * TILE_BYTES + (u & 1) * (TILE_BYTES / 4);
                if (i >= W_START) mbar_expect_tx(bar, TILE_BYTES / 2);
                tma2d_hint(dst, tm, 0, row, bar, stream_pol);
                tma2d_hint(dst + TILE_BYTES / 2, tm, 64, row, bar, stream_pol);
                if (i >= W_START) {
                    asm volatile("red.relaxed.gpu.global.add.u32 [%0], %1;" ::"l"(p.epoch + 8), "r"(i == W_START ? W_START + 1 : 1) : "memory");
                    sts32(sb + SM_PROG, i + 1);
                }
            }
            row += i == 31 ? TILE_KEYS / 2 - WIN : TILE_KEYS / 2;
            if (++u == 2 * NSLOT) u = 0;
        }
#pragma unroll 1
        for (int k = 0; k < 7; k++) {
            if (k < 2) {
#pragma unroll 1
                while (landed <= 64 + k - W_WO) {
                    mbar_wait(bars + (BAR_FULL + lu) * 8, lpar);
                    landed++;
                    if (++lu == 2 * NSLOT) { lu = 0; lpar ^= 1; }
                }
            } else {
                mbar_wait(bars + (BAR_W + k - W_END) * 8, 0);
            }
            if (k == HOLD_K) mbar_wait(bars + BAR_GO * 8, 0);
            if ((0x2b >> k) & 1) {
                mbar_wait(bars + (BAR_EMPTY + es) * 8, epar);
                if (++es == NSLOT) es = 0;
                if (es == 4) epar ^= 1;
            }
            if (leader) {
                const bool is1 = k >= 2 && k < 5;
                const CUtensorMap* tm = &p.tmWo + (k < 2 ? 0 : (is1 ? 1 : 2));
                const int4 it = p.witem[k];
                mbar_expect_tx(bars + (BAR_W + k) * 8, it.y);
                tma2d(sb + it.x, tm, is1 ? (g * 288 + j * 36) & ~7 : j * 72, g * it.z + it.w, bars + (BAR_W + k) * 8);
            }
        }
        return;
    }

    const int g8 = lane >> 2, t4 = lane & 3;
    unsigned long long* const scratch = p.scratch;
    const bool is_attn = warp < 8;
    const bool is_red = warp < 4 && g < 9;
    const int red_row = 2 * warp + ((lane >> 2) & 1);
    uint32_t hv[9];
    uint32_t res = 0;
    if (is_attn) {
        const uint32_t* xr = reinterpret_cast<const uint32_t*>(p.x + warp * D_MODEL) + lane;
#pragma unroll
        for (int i = 0; i < 9; i++) hv[i] = __ldg(xr + 32 * i);
    }
    if (is_red) res = __ldg(reinterpret_cast<const uint32_t*>(p.x + red_row * D_MODEL + j * 72 + g * 8) + t4);
    if (is_attn) {
        const __nv_bfloat16* src = p.wq + (tid >> 2) * 4096 + g * 256 + j * 32 + (tid & 3) * 8;
        uint32_t dst = sb + WQ_OFF + (tid >> 2) * 80 + (tid & 3) * 16;
#pragma unroll 1
        for (int i = 0; i < 9; i++) {
            asm volatile("cp.async.cg.shared.global [%0], [%1], 16;" ::"r"(dst), "l"(src) : "memory");
            src += 64 * 4096; dst += 64 * 80;
        }
        asm volatile("cp.async.commit_group;" ::: "memory");
    }
    uint32_t tag;
    asm volatile("ld.relaxed.gpu.global.u32 %0, [%1];" : "=r"(tag) : "l"(p.epoch) : "memory");
    const uint32_t q_out = QLL_OFF + (g * 8 + warp) * 128 + j * 16 + (lane >> 1);
    const uint32_t o_out = pin32(OLL_OFF + cta * 128 + ((lane >> 3) & 1) * 64 + warp * 8 + ((lane >> 2) & 1) * 4 + (lane & 3));
    const uint32_t part_out = pin32(HLL_OFF + ((warp * 8 + j) * 16 + g) * 64 + lane * 2);
    const uint32_t x_out = pin32(ALL_OFF + (g * 8 + tid / 36) * 144 + j * 18 + ((tid % 36) >> 1));
    const uint32_t a_src = pin32(sb + SM_SC + ((tid / 36) * 52 + tid % 36 + (j & 1) * 4) * 4);
    const uint32_t hb_out = pin32(HB_OFF + (lane >> 3) * 2304 + red_row * 288 + j * 36 + g * 4 + t4);
    const uint32_t x_in = pin32(HB_OFF + (cta % HB_COPIES) * 2304 + warp * 288 + lane);
    const uint32_t red_in = pin32(HLL_OFF + cta * 1024 + (lane >> 3) * 64 + ((warp & 3) * 8 + (lane & 7)) * 2);
    const uint32_t ln_dst = pin32(sb + SM_ACT + warp * ACT_PITCH * 2 + lane * 4);
    const uint32_t gat_dst_a = pin32(sb + SM_GAT + (tid / 36) * (A_PITCH * 2) + (tid % 36) * 16);
    if (is_attn && (lane & 1) == 0) st_pkt(scratch + q_out, 0u, 0u);
    tag += 1;
    __syncthreads();

#pragma unroll 1
    for (int ph = 0; ph < 2; ph++) {
        if (is_attn) {
            uint32_t wf[5][3][4];
            const int s0 = warp < 4 ? 5 * warp : 4 * warp + 4;
            if (ph == 0) {
                asm volatile("cp.async.wait_group 0;" ::: "memory");
                sync_attn();
            } else {
                mbar_wait_n<3>(bars + (BAR_W + 2) * 8);
            }
            {
                const uint32_t wl = sb + (ph ? W1_OFF : WQ_OFF) + (s0 * 16 + (lane & 7) + ((lane >> 4) << 3)) * 80 + ((lane >> 3) & 1) * 16;
#pragma unroll
                for (int i = 0; i < 5; i++) {
                    if (i < 4 || warp < 4) {
#pragma unroll
                        for (int m = 0; m < 3; m++) ldsm_x4_t(wf[i][m], wl + i * 16 * 80 + m * 32);
                    }
                }
            }
            if (ph == 0) {
                __syncwarp();
                if (lane == 0) { mbar_arrive(bars + (BAR_EMPTY + 4) * 8); mbar_arrive(bars + (BAR_EMPTY + 5) * 8); }
            } else {
                wait_first(scratch + x_in + 256, tag, lane, H_BACKOFF);
                poll_pkts<9, 32>(scratch + x_in, hv, tag);
            }
            layernorm_row(hv, ln_dst);
            sync_attn();
            float c[3][2][4];
#pragma unroll
            for (int m = 0; m < 3; m++) {
#pragma unroll
                for (int h = 0; h < 2; h++) { c[m][h][0] = c[m][h][1] = c[m][h][2] = c[m][h][3] = 0.f; }
            }
            uint32_t bf[5][2];
            const uint32_t bl = sb + SM_ACT + (lane & 7) * (ACT_PITCH * 2) + ((lane >> 3) & 1) * 16 + s0 * 32;
#pragma unroll
            for (int i = 0; i < 5; i++) if (i < 4 || warp < 4) ldsm_x2(bf[i][0], bf[i][1], bl + i * 32);
#pragma unroll
            for (int i = 0; i < 5; i++) {
                if (i < 4 || warp < 4) {
#pragma unroll
                    for (int m = 0; m < 3; m++) mma16816(c[m][i & 1], wf[i][m], bf[i][0], bf[i][1]);
                }
            }
            const uint32_t pw = sb + SM_SC + (warp * 8 * 52 + 2 * t4 * 52 + g8) * 4;
#pragma unroll
            for (int m = 0; m < 3; m++) {
                sts32f(pw + m * 64, c[m][0][0] + c[m][1][0]);
                sts32f(pw + m * 64 + 208, c[m][0][1] + c[m][1][1]);
                sts32f(pw + m * 64 + 32, c[m][0][2] + c[m][1][2]);
                sts32f(pw + m * 64 + 240, c[m][0][3] + c[m][1][3]);
            }
        }
        if (ph || is_attn) {
            if (ph) sync_comp(); else sync_attn();
            const uint32_t pr = ph ? a_src : sb + SM_SC + (warp * 52 + lane) * 4;
            float v[8];
#pragma unroll
            for (int w = 0; w < 8; w++) v[w] = lds32f(pr + w * (8 * 52 * 4));
            float f = ((v[0] + v[1]) + (v[2] + v[3])) + ((v[4] + v[5]) + (v[6] + v[7]));
            if (ph) f = fmaxf(f, 0.f);
            const float fn = __shfl_down_sync(0xffffffffu, f, 1);
            if ((lane & 1) == 0) st_pkt(scratch + (ph ? x_out : q_out), pack_bf16(f, fn), tag);
        }
        if (is_attn) {
            if (ph == 0) {
                if (tid < 128) {
                    uint32_t v[1];
                    poll_pkts<1, 1>(scratch + QLL_OFF + cta * 128 + tid, v, tag);
                    sts32(sb + SM_QS + ((tid & 64) + (tid & 3) * 16 + ((tid & 63) >> 2)) * 4, v[0]);
                }
                sync_attn();
                uint32_t qf[16];
#pragma unroll
                for (int s = 0; s < 4; s++) {
                    const uint4 v = lds128(sb + SM_QS + ((g8 & 1) * 64 + t4 * 16) * 4 + s * 16);
                    qf[4 * s] = v.x; qf[4 * s + 1] = v.y; qf[4 * s + 2] = v.z; qf[4 * s + 3] = v.w;
                }

                float m0 = -INFINITY, m1 = -INFINITY;
                {
                    const int krow = warp * 16 + (lane & 7) + ((lane >> 3) & 1) * 8;
                    const uint32_t rowoff = krow * 128;
                    const uint32_t chi = lane >> 4;
                    const uint32_t sw = krow & 7;
                    uint32_t slot = 0, par = 0;
                    uint32_t wsc = sb + SM_SC + ((warp >> 1) * 40 + (warp & 1) * 16 + g8) * 4;
#pragma unroll 1
                    for (int n = 0; n < NTILE; n++) {
                        mbar_wait(bars + (BAR_FULL + 2 * slot + (warp >> 2)) * 8, par);
                        const uint32_t base = sb + slot * TILE_BYTES + rowoff;
                        float c0[4] = {0.f, 0.f, 0.f, 0.f}, c1[4] = {0.f, 0.f, 0.f, 0.f};
#pragma unroll
                        for (int s = 0; s < 8; s += 2) {
                            uint32_t a[4], b[4];
                            ldsm_x4(a, base + (s >> 2) * (TILE_BYTES / 2) + ((((s & 3) * 2 + chi) ^ sw) << 4));
                            ldsm_x4(b, base + (s >> 2) * (TILE_BYTES / 2) + ((((s & 3) * 2 + 2 + chi) ^ sw) << 4));
                            mma16816(c0, a, qf[2 * s], qf[2 * s + 1]);
                            mma16816(c1, b, qf[2 * s + 2], qf[2 * s + 3]);
                        }
                        __syncwarp();
                        if (lane == 0) mbar_arrive(bars + (BAR_EMPTY + slot) * 8);
                        const float scale = 0.08838834764831845f;
                        const uint32_t u0 = pack_bf16(c0[0] + c1[0], c0[1] + c1[1]), u1 = pack_bf16(c0[2] + c1[2], c0[3] + c1[3]);
                        const uint32_t s0 = pack_bf16(bf_lo(u0) * scale, bf_hi(u0) * scale), s1 = pack_bf16(bf_lo(u1) * scale, bf_hi(u1) * scale);
                        m0 = fmaxf(m0, fmaxf(bf_lo(s0), bf_lo(s1)));
                        m1 = fmaxf(m1, fmaxf(bf_hi(s0), bf_hi(s1)));
                        if (t4 == 0) { sts32(wsc, s0); sts32(wsc + 32, s1); }
                        wsc += 4 * 40 * 4;
                        if (++slot == NSLOT) { slot = 0; par ^= 1; }
                    }
                }
                {
#pragma unroll
                    for (int o = 16; o > 2; o >>= 1) { m0 = fmaxf(m0, __shfl_xor_sync(0xffffffffu, m0, o)); m1 = fmaxf(m1, __shfl_xor_sync(0xffffffffu, m1, o)); }
                    if (lane == 0) { sts32f(sb + SM_RED + warp * 4, m0); sts32f(sb + SM_RED + 32 + warp * 4, m1); }
                    sync_attn();
                    uint2 sv[4];
#pragma unroll
                    for (int i = 0; i < 4; i++) sv[i] = lds64(sb + SM_SC + ((tid >> 2) * 40 + 2 * t4 + 8 * i) * 4);
                    sync_attn();
#pragma unroll 1
                    for (int h = 0; h < 2; h++) {
                        const uint4 a = lds128(sb + SM_RED + h * 32), b = lds128(sb + SM_RED + h * 32 + 16);
                        const float m = fmaxf(fmaxf(fmaxf(__uint_as_float(a.x), __uint_as_float(a.y)), fmaxf(__uint_as_float(a.z), __uint_as_float(a.w))),
                                              fmaxf(fmaxf(__uint_as_float(b.x), __uint_as_float(b.y)), fmaxf(__uint_as_float(b.z), __uint_as_float(b.w))));
                        const uint32_t sel = h ? 0x3244u : 0x1044u;
                        const float l2e = 1.4426950408889634f, ml = -m * l2e;
                        float e[8], sum = 0.f;
#pragma unroll
                        for (int i = 0; i < 4; i++) {
                            e[2 * i] = ex2(fmaf(__uint_as_float(__byte_perm(sv[i].x, 0u, sel)), l2e, ml));
                            e[2 * i + 1] = ex2(fmaf(__uint_as_float(__byte_perm(sv[i].y, 0u, sel)), l2e, ml));
                            sum += e[2 * i] + e[2 * i + 1];
                        }
                        sum = warp_sum(sum);
                        if (lane == 0) sts32f(sb + SM_RED + 64 + h * 32 + warp * 4, sum);
                        sync_attn();
                        const uint4 c = lds128(sb + SM_RED + 64 + h * 32), d = lds128(sb + SM_RED + 80 + h * 32);
                        const float tot = ((__uint_as_float(c.x) + __uint_as_float(c.y)) + (__uint_as_float(c.z) + __uint_as_float(c.w))) +
                                          ((__uint_as_float(d.x) + __uint_as_float(d.y)) + (__uint_as_float(d.z) + __uint_as_float(d.w)));
                        const float inv = __fdividef(1.0f, tot);
                        sts128(sb + SM_SC + h * P_HEAD_STRIDE + tid * 16, make_uint4(pack_bf16(e[0] * inv, e[1] * inv), pack_bf16(e[2] * inv, e[3] * inv),
                                                                                     pack_bf16(e[4] * inv, e[5] * inv), pack_bf16(e[6] * inv, e[7] * inv)));
                    }
                    sync_attn();
                }
                float c0[4] = {0.f, 0.f, 0.f, 0.f}, c1[4] = {0.f, 0.f, 0.f, 0.f};
                {
                    const int krow = (lane & 7) + (lane >> 4) * 8;
                    const uint32_t chunk = (warp & 3) * 2 + ((lane >> 3) & 1);
                    const uint32_t lane_off = (warp >> 2) * (TILE_BYTES / 2) + krow * 128 + ((chunk ^ (lane & 7)) << 4);
                    uint32_t pb = sb + SM_SC + (g8 & 1) * P_HEAD_STRIDE + t4 * 16;
                    uint32_t slot = NTILE % NSLOT, par = (NTILE / NSLOT) & 1;
#pragma unroll 1
                    for (int n = NTILE; n < 2 * NTILE; n++) {
                        const uint32_t base = sb + slot * TILE_BYTES + lane_off;
#pragma unroll
                        for (int s = 0; s < 8; s += 2) {
                            if ((s & 3) == 0) mbar_wait(bars + (BAR_FULL + 2 * slot + (s >> 2)) * 8, par);
                            uint32_t a[4], b[4];
                            const uint4 pv = lds128(pb + (s >> 1) * 64);
                            ldsm_x4_t(a, base + s * 2048);
                            ldsm_x4_t(b, base + (s + 1) * 2048);
                            mma16816(c0, a, pv.x, pv.y);
                            mma16816(c1, b, pv.z, pv.w);
                        }
                        __syncwarp();
                        if (lane == 0) mbar_arrive(bars + (BAR_EMPTY + slot) * 8);
                        pb += 256;
                        if (++slot == NSLOT) { slot = 0; par ^= 1; }
                        if (n == PREWRITE_TILE) {
                            if (lane < 16) st_pkt(scratch + o_out, 0u, 0u);
                            st_pkt2(scratch + part_out, 0u, 0u, 0u); st_pkt2(scratch + part_out + (YLL_OFF - HLL_OFF), 0u, 0u, 0u);
                            if ((lane & 1) == 0) st_pkt(scratch + x_out, 0u, 0u);
                            if (is_red) st_pkt(scratch + hb_out, 0u, 0u);
                            if (warp == 0) asm volatile("bar.arrive 3, 64;" ::: "memory");
                        }
                    }
                }
                const uint32_t pa = pack_bf16(c0[0] + c1[0], c0[1] + c1[1]);
                const uint32_t pb2 = pack_bf16(c0[2] + c1[2], c0[3] + c1[3]);
                const int src = (lane & 3) * 8;
                const uint32_t a0 = __shfl_sync(0xffffffffu, pa, src), a1 = __shfl_sync(0xffffffffu, pa, src + 4);
                const uint32_t b0 = __shfl_sync(0xffffffffu, pb2, src), b1 = __shfl_sync(0xffffffffu, pb2, src + 4);
                const uint32_t lo = (lane & 4) ? b0 : a0, hi = (lane & 4) ? b1 : a1;
                if (lane < 16) st_pkt(scratch + o_out, __byte_perm(lo, hi, (lane & 8) ? 0x7632 : 0x5410), tag);
            }
        } else if (ph == 0) {
            if (lane == 0) {
                const uint32_t base = (tag - 1) * (NCTA * 64);
                uint32_t own, n = 0;
                do {
                    uint32_t tot;
                    asm volatile("ld.relaxed.gpu.global.u32 %0, [%1];" : "=r"(tot) : "l"(p.epoch + 8) : "memory");
                    own = lds32(sb + SM_PROG);
                    const int lead = (int)(own * NCTA) - (int)(tot - base);
                    int w = W_BULK - (lead * BAL_GAIN + (lead >= 0 ? 64 * 16 : -64 * 16)) / (NCTA * 16);
                    w = w < W_MIN ? W_MIN : (w > W_MAX ? W_MAX : w);
                    asm volatile("st.volatile.shared.b32 [%0], %1;" ::"r"(sb + SM_WDYN), "r"(w) : "memory");
                    __nanosleep(BAL_SLEEP);
                } while (own < 60 && ++n < 100000);
            }
            __syncwarp();
            asm volatile("bar.sync 3, 64;" ::: "memory");
            if ((lane & 1) == 0) st_pkt(scratch + x_out, 0u, 0u);
            st_pkt2(scratch + part_out, 0u, 0u, 0u); st_pkt2(scratch + part_out + (YLL_OFF - HLL_OFF), 0u, 0u, 0u);
        }

        {
            float o0, o1;
            uint32_t wf[36];
            mbar_wait_n<2>(bars + (BAR_W + 5 * ph) * 8);
            load_wfrags<18, 144>(wf, sb + (ph ? W2_OFF : WO_OFF) + lane * 144 + warp * 16);
            if (ph || is_attn) {
                uint32_t v[4];
                const unsigned long long* src = scratch + ((ph ? ALL_OFF + g * 1152 : OLL_OFF + g * 1024) + tid * 4);
                poll_pairs<2, 2>(src, v, tag, ph ? 0 : O_BACKOFF);
                sts128(ph ? gat_dst_a : sb + SM_GAT + warp * (A_PITCH * 2) + lane * 16, make_uint4(v[0], v[1], v[2], v[3]));
            }
            sync_comp();
            if (ph == 0 && tid == 0) mbar_arrive(bars + BAR_GO * 8);
            gemm_tile<9, 9, 2>(o0, o1, wf, sb + SM_GAT + act_lane_off<A_PITCH * 2>(lane), ph ? 9 : 8);
            st_pkt2(scratch + (part_out + (ph ? YLL_OFF - HLL_OFF : 0)), __float_as_uint(o0), __float_as_uint(o1), tag);
        }
        if (is_red) {
            uint32_t v[8];
            spin_cycles(ph ? RED_DELAY1 : RED_DELAY0);
            poll_pairs<4, 256>(scratch + (red_in + (ph ? YLL_OFF - HLL_OFF : 0)), v, tag);
            float s0 = (__uint_as_float(v[0]) + __uint_as_float(v[2])) + (__uint_as_float(v[4]) + __uint_as_float(v[6]));
            float s1 = (__uint_as_float(v[1]) + __uint_as_float(v[3])) + (__uint_as_float(v[5]) + __uint_as_float(v[7]));
            s0 += __shfl_xor_sync(0xffffffffu, s0, 8); s1 += __shfl_xor_sync(0xffffffffu, s1, 8);
            s0 += __shfl_xor_sync(0xffffffffu, s0, 16); s1 += __shfl_xor_sync(0xffffffffu, s1, 16);
            const uint32_t t = pack_bf16(s0, s1);
            res = pack_bf16(bf_lo(res) + bf_lo(t), bf_hi(res) + bf_hi(t));
            if (ph == 0) {
                st_pkt(scratch + hb_out, res, tag);
            } else {
                if (lane < 8) *reinterpret_cast<uint32_t*>(p.out + red_row * D_MODEL + j * 72 + g * 8 + 2 * t4) = res;
                if (cta == 0 && tid == 0) asm volatile("st.relaxed.gpu.global.u32 [%0], %1;" ::"l"(p.epoch), "r"(tag) : "memory");
            }
        }
    }
}

typedef CUresult (*EncodeTiledFn)(CUtensorMap*, CUtensorMapDataType, cuuint32_t, void*, const cuuint64_t*, const cuuint64_t*,
                                  const cuuint32_t*, const cuuint32_t*, CUtensorMapInterleave, CUtensorMapSwizzle,
                                  CUtensorMapL2promotion, CUtensorMapFloatOOBfill);

void make_map(EncodeTiledFn enc, CUtensorMap* tm, const void* ptr, uint64_t cols, uint64_t rows, uint32_t box_cols, uint32_t box_rows,
              CUtensorMapSwizzle sw) {
    cuuint64_t gd[2] = {cols, rows};
    cuuint64_t gs[1] = {cols * 2};
    cuuint32_t bd[2] = {box_cols, box_rows};
    cuuint32_t es[2] = {1, 1};
    enc(tm, CU_TENSOR_MAP_DATA_TYPE_BFLOAT16, 2, const_cast<void*>(ptr), gd, gs, bd, es, CU_TENSOR_MAP_INTERLEAVE_NONE, sw,
        sw == CU_TENSOR_MAP_SWIZZLE_NONE ? CU_TENSOR_MAP_L2_PROMOTION_L2_128B : CU_TENSOR_MAP_L2_PROMOTION_L2_256B, CU_TENSOR_MAP_FLOAT_OOB_FILL_NONE);
}

}


extern "C" void kernel_launch(void* const* d_in, const int* in_sizes, int n_in, void* d_out, int out_size) {
    (void)in_sizes; (void)n_in; (void)out_size;
    static EncodeTiledFn enc = nullptr;
    static unsigned long long* scratch = nullptr;
    static unsigned int* epoch = nullptr;
    if (!enc) {
        cudaDriverEntryPointQueryResult qr;
        void* fn = nullptr;
        cudaGetDriverEntryPoint("cuTensorMapEncodeTiled", &fn, cudaEnableDefault, &qr);
        enc = (EncodeTiledFn)fn;
        cudaFuncSetAttribute(fused_decode_kernel, cudaFuncAttributeMaxDynamicSharedMemorySize, SMEM_BYTES);
        cudaGetSymbolAddress((void**)&scratch, g_scratch);
        cudaGetSymbolAddress((void**)&epoch, g_epoch);
    }
    Params p;
    make_map(enc, &p.tmK, d_in[1], 128, 8ull * 16 * SK, 64, TILE_KEYS / 2, CU_TENSOR_MAP_SWIZZLE_128B);
    make_map(enc, &p.tmV, d_in[2], 128, 8ull * 16 * SK, 64, TILE_KEYS / 2, CU_TENSOR_MAP_SWIZZLE_128B);
    make_map(enc, &p.tmWo, d_in[4], 576, 4096, 72, 128, CU_TENSOR_MAP_SWIZZLE_NONE);
    make_map(enc, &p.tmW1, d_in[6], 4608, 576, 40, 192, CU_TENSOR_MAP_SWIZZLE_NONE);
    make_map(enc, &p.tmW2, d_in[7], 576, 4608, 72, 144, CU_TENSOR_MAP_SWIZZLE_NONE);
    for (int k = 0; k < 7; k++) {
        if (k < 2) p.witem[k] = make_int4(WO_OFF + k * 128 * 144, 128 * 144, 256, k * 128);
        else if (k < 5) p.witem[k] = make_int4(W1_OFF + (k - 2) * 192 * 80, 192 * 80, 0, (k - 2) * 192);
        else p.witem[k] = make_int4(W2_OFF + (k - 5) * 144 * 144, 144 * 144, 288, (k - 5) * 144);
    }
    p.x = (const __nv_bfloat16*)d_in[0];
    p.wq = (const __nv_bfloat16*)d_in[3];
    p.out = (__nv_bfloat16*)d_out;
    p.scratch = scratch;
    p.epoch = epoch;
    fused_decode_kernel<<<NCTA, NTHREADS, SMEM_BYTES, cudaStreamPerThread>>>(p);
}
```
